```python
import torch

def _softmax(x, axis=-1):
    return torch.softmax(x, dim=axis)
def _gelu(x):
    return torch.nn.functional.gelu(x, approximate="tanh")
def _silu(x):
    return torch.nn.functional.silu(x)
def _sigmoid(x):
    return torch.sigmoid(x)
def _layernorm(x, axis=-1, eps=1e-5):
    m = x.mean(dim=axis, keepdim=True)
    v = x.var(dim=axis, keepdim=True, unbiased=False)
    return (x - m) / torch.sqrt(v + eps)
def _scatter_add(tgt, idx, src, axis=0):
    return tgt.clone().index_add_(axis, idx, src)
def _segment_sum(src, seg, n):
    out = torch.zeros((n,) + src.shape[1:], dtype=src.dtype)
    return out.index_add_(0, seg, src)
def _pad(x, pw):
    flat = tuple(v for pair in reversed(pw) for v in pair)
    return torch.nn.functional.pad(x, flat)

kernel_name = 'recurrent_scan__spectral_fnet__mixer_channel_mlp__prompt'

def setup_inputs():

    _w = (lambda a: (lambda t: t.to(torch.bfloat16) if t.is_floating_point() else t)(torch.as_tensor(a)))
    def _A_setup():
        B, S, D = 1, 2048, 512
        ns = torch.arange(S)[:, None] * torch.arange(S)[None, :]
        nd = torch.arange(D)[:, None] * torch.arange(D)[None, :]
        Ws_re = torch.cos(-2.0 * torch.pi * ns / S).to(float)
        Ws_im = torch.sin(-2.0 * torch.pi * ns / S).to(float)
        Wd_re = torch.cos(-2.0 * torch.pi * nd / D).to(float)
        Wd_im = torch.sin(-2.0 * torch.pi * nd / D).to(float)
        return {
            "x": _w((lambda *s: torch.randn(*s, dtype=torch.bfloat16) * 0.05)(B, S, D)),
            "dft_seq_re": _w(Ws_re),
            "dft_seq_im": _w(Ws_im),
            "dft_hid_re": _w(Wd_re),
            "dft_hid_im": _w(Wd_im),
        }
    _A_in = _A_setup()

    def _B_setup():
        B, S, D, F = 1, 2048, 512, 1792
        return {
            "x": _w((lambda *s: torch.randn(*s, dtype=torch.bfloat16) * 0.05)(B, S, D)),
            "w1": _w((lambda *s: torch.randn(*s, dtype=torch.bfloat16) * 0.8)(D, F) * (D ** -0.5)),
            "b1": _w((lambda *s: torch.randn(*s, dtype=torch.bfloat16) * 0.4)(F)),
            "w2": _w((lambda *s: torch.randn(*s, dtype=torch.bfloat16) * 0.05)(F, D) * (F ** -0.5)),
            "b2": _w((lambda *s: torch.randn(*s, dtype=torch.bfloat16) * 0.05)(D)),
        }
    _B_in = _B_setup()

    return {
        "A_x": _A_in["x"],
        "A_dft_seq_re": _A_in["dft_seq_re"],
        "A_dft_seq_im": _A_in["dft_seq_im"],
        "A_dft_hid_re": _A_in["dft_hid_re"],
        "A_dft_hid_im": _A_in["dft_hid_im"],
        "B_x": _B_in["x"],
        "B_w1": _B_in["w1"],
        "B_b1": _B_in["b1"],
        "B_w2": _B_in["w2"],
        "B_b2": _B_in["b2"],
    }

def reference(A_x, A_dft_seq_re, A_dft_seq_im, A_dft_hid_re, A_dft_hid_im, B_x, B_w1, B_b1, B_w2, B_b2):
    def _A_ref(x, dft_seq_re, dft_seq_im, dft_hid_re, dft_hid_im):
        a = torch.einsum("bsd,ed->bse", x, dft_hid_re)
        b = torch.einsum("bsd,ed->bse", x, dft_hid_im)
        y = torch.einsum("ts,bse->bte", dft_seq_re, a) - torch.einsum("ts,bse->bte", dft_seq_im, b)
        return y

    def _B_ref(x, w1, b1, w2, b2):
        y = _layernorm(x, axis=-1)
        h = _gelu(torch.einsum("bsd,df->bsf", y, w1) + b1)
        return torch.einsum("bsf,fd->bsd", h, w2) + b2

    x = A_x
    xn = _layernorm(x, axis=-1)
    s = _A_ref(xn, A_dft_seq_re, A_dft_seq_im, A_dft_hid_re, A_dft_hid_im)
    g = _silu(_B_ref(xn, B_w1, B_b1, B_w2, B_b2))
    return x + s * g
```

```cpp
#include <cuda_runtime.h>
#include <cuda_bf16.h>
#include <cuda.h>
#include <stdint.h>

namespace {

constexpr int SEQ = 2048, DM = 512, FF = 1792;
constexpr int NST = 6;
constexpr int STB = 32768;
constexpr int OFF_G = NST * STB;
constexpr int OFF_STATS = OFF_G + 16384;
constexpr int OFF_VAB = OFF_STATS + 2048;
constexpr int OFF_VH = OFF_VAB + 512;
constexpr int OFF_B2 = OFF_VH + 1792;
constexpr int OFF_BAR = OFF_B2 + 512;
constexpr int SMEM_BYTES = OFF_BAR + 128;
constexpr int BAR_FULL = 0, BAR_EMPTY = 48, BAR_VEC = 96, BAR_G = 104, BAR_Y = 112, BAR_OK = 120;
constexpr int NSTEPS = 70;
constexpr int LAND_STAGE = (NSTEPS - 6) % NST;

constexpr int C_DONE = 0, C_PREP = 32, C_AB = 64, C_H = 64 + 8 * 32;

struct Params {
  CUtensorMap mx, mdre, mdim, mw1, mcr, mci, mab, mh, mw2;
  const __nv_bfloat16 *x, *dre, *dim, *w1, *b1, *w2, *b2;
  __nv_bfloat16* out;
};

__device__ __align__(1024) __nv_bfloat16 g_ab[2 * SEQ * DM];
__device__ __align__(1024) __nv_bfloat16 g_h[SEQ * FF];
__device__ float4 g_stats[SEQ];
__device__ __align__(16) float g_cs[2 * DM + FF];
__device__ unsigned g_cnt[64 + 8 * 32 + 16 * 32];
#define TLREC(ev) do {} while (0)
#define TLC(ev) do {} while (0)

__device__ __forceinline__ void mbar_init(uint32_t bar, uint32_t cnt) { asm volatile("mbarrier.init.shared::cta.b64 [%0], %1;" :: "r"(bar), "r"(cnt) : "memory"); }
__device__ __forceinline__ void mbar_expect_tx(uint32_t bar, uint32_t bytes) { asm volatile("mbarrier.arrive.expect_tx.shared::cta.b64 _, [%0], %1;" :: "r"(bar), "r"(bytes) : "memory"); }
__device__ __forceinline__ void mbar_arrive(uint32_t bar) { asm volatile("mbarrier.arrive.shared::cta.b64 _, [%0];" :: "r"(bar) : "memory"); }
__device__ __forceinline__ void mbar_arrive_cluster(uint32_t remote_bar) { asm volatile("mbarrier.arrive.shared::cluster.b64 _, [%0];" :: "r"(remote_bar) : "memory"); }
__device__ __forceinline__ uint32_t mapa(uint32_t addr, uint32_t cta) { uint32_t r; asm("mapa.shared::cluster.u32 %0, %1, %2;" : "=r"(r) : "r"(addr), "r"(cta)); return r; }
__device__ __forceinline__ bool mbar_try(uint32_t bar, uint32_t parity) {
  uint32_t ok;
  asm volatile("{\n.reg .pred p;\nmbarrier.try_wait.parity.shared::cta.b64 p, [%1], %2;\nselp.u32 %0, 1, 0, p;\n}" : "=r"(ok) : "r"(bar), "r"(parity) : "memory");
  return ok;
}
__device__ __forceinline__ void mbar_wait(uint32_t bar, uint32_t parity) {
  if (mbar_try(bar, parity)) return;
  uint32_t n = 0;
  while (!mbar_try(bar, parity)) { if (++n > (1u << 20)) __trap(); }
}
__device__ __forceinline__ bool elect_one() {
  uint32_t p;
  asm volatile("{\n.reg .pred p;\nelect.sync _|p, 0xffffffff;\nselp.u32 %0, 1, 0, p;\n}" : "=r"(p));
  return p;
}
__device__ __forceinline__ void tma2d(uint32_t dst, const CUtensorMap* m, int c0, int c1, uint32_t bar) {
  asm volatile("cp.async.bulk.tensor.2d.shared::cluster.global.mbarrier::complete_tx::bytes [%0], [%1, {%3, %4}], [%2];"
    :: "r"(dst), "l"(m), "r"(bar), "r"(c0), "r"(c1) : "memory");
}
__device__ __forceinline__ void tma3d(uint32_t dst, const CUtensorMap* m, int c0, int c1, int c2, uint32_t bar) {
  asm volatile("cp.async.bulk.tensor.3d.shared::cluster.global.mbarrier::complete_tx::bytes [%0], [%1, {%3, %4, %5}], [%2];"
    :: "r"(dst), "l"(m), "r"(bar), "r"(c0), "r"(c1), "r"(c2) : "memory");
}
__device__ __forceinline__ void tma5d(uint32_t dst, const CUtensorMap* m, int c0, int c4, uint32_t bar) {
  asm volatile("cp.async.bulk.tensor.5d.shared::cluster.global.mbarrier::complete_tx::bytes [%0], [%1, {%3, %5, %5, %5, %4}], [%2];"
    :: "r"(dst), "l"(m), "r"(bar), "r"(c0), "r"(c4), "r"(0) : "memory");
}
__device__ __forceinline__ void tma_pf2d(const CUtensorMap* m, int c0, int c1) {
  asm volatile("cp.async.bulk.prefetch.tensor.2d.L2.global [%0, {%1, %2}];" :: "l"(m), "r"(c0), "r"(c1) : "memory");
}
__device__ __forceinline__ void wg_fence() { asm volatile("wgmma.fence.sync.aligned;" ::: "memory"); }
__device__ __forceinline__ void wg_commit() { asm volatile("wgmma.commit_group.sync.aligned;" ::: "memory"); }
template <int N> __device__ __forceinline__ void wg_wait() { asm volatile("wgmma.wait_group.sync.aligned %0;" :: "n"(N) : "memory"); }
template <int N> __device__ __forceinline__ void reg_fence(float (&d)[N]) {
#pragma unroll
  for (int i = 0; i < N; i++) asm volatile("" : "+f"(d[i]) :: "memory");
}
__device__ __forceinline__ void wgmma4_n128_tb0(float (&d)[64], uint32_t a, uint32_t b, int scale_d) {
  asm volatile("{\n.reg .pred p;\n.reg .b32 la, lb, hi;\n.reg .b64 da, db;\nsetp.ne.b32 p, %66, 0;\nmov.b32 hi, 0x40000040;\n"
    "add.u32 la, %64, 0;\nadd.u32 lb, %65, 0;\nmov.b64 da, {la, hi};\nmov.b64 db, {lb, hi};\n"
    "wgmma.mma_async.sync.aligned.m64n128k16.f32.bf16.bf16 "
    "{%0, %1, %2, %3, %4, %5, %6, %7, %8, %9, %10, %11, %12, %13, %14, %15, %16, %17, %18, %19, %20, %21, %22, %23, %24, %25, %26, %27, %28, %29, %30, %31, %32, %33, %34, %35, %36, %37, %38, %39, %40, %41, %42, %43, %44, %45, %46, %47, %48, %49, %50, %51, %52, %53, %54, %55, %56, %57, %58, %59, %60, %61, %62, %63}, "
    "da, db, p, 1, 1, 0, 0;\n"
    "add.u32 la, %64, 2;\nadd.u32 lb, %65, 2;\nmov.b64 da, {la, hi};\nmov.b64 db, {lb, hi};\n"
    "wgmma.mma_async.sync.aligned.m64n128k16.f32.bf16.bf16 "
    "{%0, %1, %2, %3, %4, %5, %6, %7, %8, %9, %10, %11, %12, %13, %14, %15, %16, %17, %18, %19, %20, %21, %22, %23, %24, %25, %26, %27, %28, %29, %30, %31, %32, %33, %34, %35, %36, %37, %38, %39, %40, %41, %42, %43, %44, %45, %46, %47, %48, %49, %50, %51, %52, %53, %54, %55, %56, %57, %58, %59, %60, %61, %62, %63}, "
    "da, db, 1, 1, 1, 0, 0;\n"
    "add.u32 la, %64, 4;\nadd.u32 lb, %65, 4;\nmov.b64 da, {la, hi};\nmov.b64 db, {lb, hi};\n"
    "wgmma.mma_async.sync.aligned.m64n128k16.f32.bf16.bf16 "
    "{%0, %1, %2, %3, %4, %5, %6, %7, %8, %9, %10, %11, %12, %13, %14, %15, %16, %17, %18, %19, %20, %21, %22, %23, %24, %25, %26, %27, %28, %29, %30, %31, %32, %33, %34, %35, %36, %37, %38, %39, %40, %41, %42, %43, %44, %45, %46, %47, %48, %49, %50, %51, %52, %53, %54, %55, %56, %57, %58, %59, %60, %61, %62, %63}, "
    "da, db, 1, 1, 1, 0, 0;\n"
    "add.u32 la, %64, 6;\nadd.u32 lb, %65, 6;\nmov.b64 da, {la, hi};\nmov.b64 db, {lb, hi};\n"
    "wgmma.mma_async.sync.aligned.m64n128k16.f32.bf16.bf16 "
    "{%0, %1, %2, %3, %4, %5, %6, %7, %8, %9, %10, %11, %12, %13, %14, %15, %16, %17, %18, %19, %20, %21, %22, %23, %24, %25, %26, %27, %28, %29, %30, %31, %32, %33, %34, %35, %36, %37, %38, %39, %40, %41, %42, %43, %44, %45, %46, %47, %48, %49, %50, %51, %52, %53, %54, %55, %56, %57, %58, %59, %60, %61, %62, %63}, "
    "da, db, 1, 1, 1, 0, 0;\n"
    "}\n"
    : "+f"(d[0]), "+f"(d[1]), "+f"(d[2]), "+f"(d[3]), "+f"(d[4]), "+f"(d[5]), "+f"(d[6]), "+f"(d[7]), "+f"(d[8]), "+f"(d[9]), "+f"(d[10]), "+f"(d[11]), "+f"(d[12]), "+f"(d[13]), "+f"(d[14]), "+f"(d[15]), "+f"(d[16]), "+f"(d[17]), "+f"(d[18]), "+f"(d[19]), "+f"(d[20]), "+f"(d[21]), "+f"(d[22]), "+f"(d[23]), "+f"(d[24]), "+f"(d[25]), "+f"(d[26]), "+f"(d[27]), "+f"(d[28]), "+f"(d[29]), "+f"(d[30]), "+f"(d[31]), "+f"(d[32]), "+f"(d[33]), "+f"(d[34]), "+f"(d[35]), "+f"(d[36]), "+f"(d[37]), "+f"(d[38]), "+f"(d[39]), "+f"(d[40]), "+f"(d[41]), "+f"(d[42]), "+f"(d[43]), "+f"(d[44]), "+f"(d[45]), "+f"(d[46]), "+f"(d[47]), "+f"(d[48]), "+f"(d[49]), "+f"(d[50]), "+f"(d[51]), "+f"(d[52]), "+f"(d[53]), "+f"(d[54]), "+f"(d[55]), "+f"(d[56]), "+f"(d[57]), "+f"(d[58]), "+f"(d[59]), "+f"(d[60]), "+f"(d[61]), "+f"(d[62]), "+f"(d[63])
    : "r"(a), "r"(b), "r"(scale_d));
}
__device__ __forceinline__ void wgmma4_n128_tb1(float (&d)[64], uint32_t a, uint32_t b, int scale_d) {
  asm volatile("{\n.reg .pred p;\n.reg .b32 la, lb, hi;\n.reg .b64 da, db;\nsetp.ne.b32 p, %66, 0;\nmov.b32 hi, 0x40000040;\n"
    "add.u32 la, %64, 0;\nadd.u32 lb, %65, 0;\nmov.b64 da, {la, hi};\nmov.b64 db, {lb, hi};\n"
    "wgmma.mma_async.sync.aligned.m64n128k16.f32.bf16.bf16 "
    "{%0, %1, %2, %3, %4, %5, %6, %7, %8, %9, %10, %11, %12, %13, %14, %15, %16, %17, %18, %19, %20, %21, %22, %23, %24, %25, %26, %27, %28, %29, %30, %31, %32, %33, %34, %35, %36, %37, %38, %39, %40, %41, %42, %43, %44, %45, %46, %47, %48, %49, %50, %51, %52, %53, %54, %55, %56, %57, %58, %59, %60, %61, %62, %63}, "
    "da, db, p, 1, 1, 0, 1;\n"
    "add.u32 la, %64, 2;\nadd.u32 lb, %65, 128;\nmov.b64 da, {la, hi};\nmov.b64 db, {lb, hi};\n"
    "wgmma.mma_async.sync.aligned.m64n128k16.f32.bf16.bf16 "
    "{%0, %1, %2, %3, %4, %5, %6, %7, %8, %9, %10, %11, %12, %13, %14, %15, %16, %17, %18, %19, %20, %21, %22, %23, %24, %25, %26, %27, %28, %29, %30, %31, %32, %33, %34, %35, %36, %37, %38, %39, %40, %41, %42, %43, %44, %45, %46, %47, %48, %49, %50, %51, %52, %53, %54, %55, %56, %57, %58, %59, %60, %61, %62, %63}, "
    "da, db, 1, 1, 1, 0, 1;\n"
    "add.u32 la, %64, 4;\nadd.u32 lb, %65, 256;\nmov.b64 da, {la, hi};\nmov.b64 db, {lb, hi};\n"
    "wgmma.mma_async.sync.aligned.m64n128k16.f32.bf16.bf16 "
    "{%0, %1, %2, %3, %4, %5, %6, %7, %8, %9, %10, %11, %12, %13, %14, %15, %16, %17, %18, %19, %20, %21, %22, %23, %24, %25, %26, %27, %28, %29, %30, %31, %32, %33, %34, %35, %36, %37, %38, %39, %40, %41, %42, %43, %44, %45, %46, %47, %48, %49, %50, %51, %52, %53, %54, %55, %56, %57, %58, %59, %60, %61, %62, %63}, "
    "da, db, 1, 1, 1, 0, 1;\n"
    "add.u32 la, %64, 6;\nadd.u32 lb, %65, 384;\nmov.b64 da, {la, hi};\nmov.b64 db, {lb, hi};\n"
    "wgmma.mma_async.sync.aligned.m64n128k16.f32.bf16.bf16 "
    "{%0, %1, %2, %3, %4, %5, %6, %7, %8, %9, %10, %11, %12, %13, %14, %15, %16, %17, %18, %19, %20, %21, %22, %23, %24, %25, %26, %27, %28, %29, %30, %31, %32, %33, %34, %35, %36, %37, %38, %39, %40, %41, %42, %43, %44, %45, %46, %47, %48, %49, %50, %51, %52, %53, %54, %55, %56, %57, %58, %59, %60, %61, %62, %63}, "
    "da, db, 1, 1, 1, 0, 1;\n"
    "}\n"
    : "+f"(d[0]), "+f"(d[1]), "+f"(d[2]), "+f"(d[3]), "+f"(d[4]), "+f"(d[5]), "+f"(d[6]), "+f"(d[7]), "+f"(d[8]), "+f"(d[9]), "+f"(d[10]), "+f"(d[11]), "+f"(d[12]), "+f"(d[13]), "+f"(d[14]), "+f"(d[15]), "+f"(d[16]), "+f"(d[17]), "+f"(d[18]), "+f"(d[19]), "+f"(d[20]), "+f"(d[21]), "+f"(d[22]), "+f"(d[23]), "+f"(d[24]), "+f"(d[25]), "+f"(d[26]), "+f"(d[27]), "+f"(d[28]), "+f"(d[29]), "+f"(d[30]), "+f"(d[31]), "+f"(d[32]), "+f"(d[33]), "+f"(d[34]), "+f"(d[35]), "+f"(d[36]), "+f"(d[37]), "+f"(d[38]), "+f"(d[39]), "+f"(d[40]), "+f"(d[41]), "+f"(d[42]), "+f"(d[43]), "+f"(d[44]), "+f"(d[45]), "+f"(d[46]), "+f"(d[47]), "+f"(d[48]), "+f"(d[49]), "+f"(d[50]), "+f"(d[51]), "+f"(d[52]), "+f"(d[53]), "+f"(d[54]), "+f"(d[55]), "+f"(d[56]), "+f"(d[57]), "+f"(d[58]), "+f"(d[59]), "+f"(d[60]), "+f"(d[61]), "+f"(d[62]), "+f"(d[63])
    : "r"(a), "r"(b), "r"(scale_d));
}
__device__ __forceinline__ void wgmma4_n96_tb1(float (&d)[48], uint32_t a, uint32_t b, int scale_d) {
  asm volatile("{\n.reg .pred p;\n.reg .b32 la, lb, hi;\n.reg .b64 da, db;\nsetp.ne.b32 p, %50, 0;\nmov.b32 hi, 0x40000040;\n"
    "add.u32 la, %48, 0;\nadd.u32 lb, %49, 0;\nmov.b64 da, {la, hi};\nmov.b64 db, {lb, hi};\n"
    "wgmma.mma_async.sync.aligned.m64n96k16.f32.bf16.bf16 "
    "{%0, %1, %2, %3, %4, %5, %6, %7, %8, %9, %10, %11, %12, %13, %14, %15, %16, %17, %18, %19, %20, %21, %22, %23, %24, %25, %26, %27, %28, %29, %30, %31, %32, %33, %34, %35, %36, %37, %38, %39, %40, %41, %42, %43, %44, %45, %46, %47}, "
    "da, db, p, 1, 1, 0, 1;\n"
    "add.u32 la, %48, 2;\nadd.u32 lb, %49, 128;\nmov.b64 da, {la, hi};\nmov.b64 db, {lb, hi};\n"
    "wgmma.mma_async.sync.aligned.m64n96k16.f32.bf16.bf16 "
    "{%0, %1, %2, %3, %4, %5, %6, %7, %8, %9, %10, %11, %12, %13, %14, %15, %16, %17, %18, %19, %20, %21, %22, %23, %24, %25, %26, %27, %28, %29, %30, %31, %32, %33, %34, %35, %36, %37, %38, %39, %40, %41, %42, %43, %44, %45, %46, %47}, "
    "da, db, 1, 1, 1, 0, 1;\n"
    "add.u32 la, %48, 4;\nadd.u32 lb, %49, 256;\nmov.b64 da, {la, hi};\nmov.b64 db, {lb, hi};\n"
    "wgmma.mma_async.sync.aligned.m64n96k16.f32.bf16.bf16 "
    "{%0, %1, %2, %3, %4, %5, %6, %7, %8, %9, %10, %11, %12, %13, %14, %15, %16, %17, %18, %19, %20, %21, %22, %23, %24, %25, %26, %27, %28, %29, %30, %31, %32, %33, %34, %35, %36, %37, %38, %39, %40, %41, %42, %43, %44, %45, %46, %47}, "
    "da, db, 1, 1, 1, 0, 1;\n"
    "add.u32 la, %48, 6;\nadd.u32 lb, %49, 384;\nmov.b64 da, {la, hi};\nmov.b64 db, {lb, hi};\n"
    "wgmma.mma_async.sync.aligned.m64n96k16.f32.bf16.bf16 "
    "{%0, %1, %2, %3, %4, %5, %6, %7, %8, %9, %10, %11, %12, %13, %14, %15, %16, %17, %18, %19, %20, %21, %22, %23, %24, %25, %26, %27, %28, %29, %30, %31, %32, %33, %34, %35, %36, %37, %38, %39, %40, %41, %42, %43, %44, %45, %46, %47}, "
    "da, db, 1, 1, 1, 0, 1;\n"
    "}\n"
    : "+f"(d[0]), "+f"(d[1]), "+f"(d[2]), "+f"(d[3]), "+f"(d[4]), "+f"(d[5]), "+f"(d[6]), "+f"(d[7]), "+f"(d[8]), "+f"(d[9]), "+f"(d[10]), "+f"(d[11]), "+f"(d[12]), "+f"(d[13]), "+f"(d[14]), "+f"(d[15]), "+f"(d[16]), "+f"(d[17]), "+f"(d[18]), "+f"(d[19]), "+f"(d[20]), "+f"(d[21]), "+f"(d[22]), "+f"(d[23]), "+f"(d[24]), "+f"(d[25]), "+f"(d[26]), "+f"(d[27]), "+f"(d[28]), "+f"(d[29]), "+f"(d[30]), "+f"(d[31]), "+f"(d[32]), "+f"(d[33]), "+f"(d[34]), "+f"(d[35]), "+f"(d[36]), "+f"(d[37]), "+f"(d[38]), "+f"(d[39]), "+f"(d[40]), "+f"(d[41]), "+f"(d[42]), "+f"(d[43]), "+f"(d[44]), "+f"(d[45]), "+f"(d[46]), "+f"(d[47])
    : "r"(a), "r"(b), "r"(scale_d));
}

__device__ __forceinline__ void bar_arrive(int id, int n) { asm volatile("bar.arrive %0, %1;" :: "r"(id), "r"(n) : "memory"); }
__device__ __forceinline__ void bar_sync(int id, int n) { asm volatile("bar.sync %0, %1;" :: "r"(id), "r"(n) : "memory"); }
__device__ __forceinline__ unsigned ld_acq(const unsigned* p) { unsigned v; asm volatile("ld.acquire.gpu.global.u32 %0, [%1];" : "=r"(v) : "l"(p) : "memory"); return v; }
__device__ __forceinline__ unsigned ld_rlx(const unsigned* p) { unsigned v; asm volatile("ld.relaxed.gpu.global.u32 %0, [%1];" : "=r"(v) : "l"(p) : "memory"); return v; }
__device__ __forceinline__ void red_rel(unsigned* p) { asm volatile("fence.acq_rel.gpu;\nred.relaxed.gpu.global.add.u32 [%0], 1;" :: "l"(p) : "memory"); }
__device__ __forceinline__ void wait_cnt(const unsigned* p, unsigned target) {
  uint32_t n = 0;
  while ((int)(ld_acq(p) - target) < 0) { if (++n > (1u << 20)) __trap(); }
}
__device__ __forceinline__ float bf_lo(uint32_t v) { return __uint_as_float(v << 16); }
__device__ __forceinline__ float bf_hi(uint32_t v) { return __uint_as_float(v & 0xffff0000u); }
__device__ __forceinline__ uint32_t pack2(float lo, float hi) { uint32_t r; asm("cvt.rn.bf16x2.f32 %0, %1, %2;" : "=r"(r) : "f"(hi), "f"(lo)); return r; }
__device__ __forceinline__ float bfr(float v) { return __bfloat162float(__float2bfloat16_rn(v)); }
__device__ __forceinline__ float ex2f(float v) { float r; asm("ex2.approx.ftz.f32 %0, %1;" : "=f"(r) : "f"(v)); return r; }
__device__ __forceinline__ float rcpf(float v) { float r; asm("rcp.approx.ftz.f32 %0, %1;" : "=f"(r) : "f"(v)); return r; }
__device__ __forceinline__ float gelu_f(float t) {
  const float c0 = -2.0f * 0.7978845608028654f * 1.4426950408889634f, c1 = c0 * 0.044715f;
  float z = t * fmaf(t * t, c1, c0);
  return t * rcpf(1.0f + ex2f(z));
}
__device__ __forceinline__ float silu_f(float z) { return z * rcpf(1.0f + ex2f(-1.4426950408889634f * z)); }
__device__ __forceinline__ uint4 ldg_nc(const void* p) { uint4 v; asm volatile("ld.global.nc.v4.u32 {%0,%1,%2,%3}, [%4];" : "=r"(v.x), "=r"(v.y), "=r"(v.z), "=r"(v.w) : "l"(p)); return v; }
__device__ __forceinline__ void stg4(void* p, uint32_t a, uint32_t b, uint32_t c, uint32_t d) { asm volatile("st.global.v4.u32 [%0], {%1,%2,%3,%4};" :: "l"(p), "r"(a), "r"(b), "r"(c), "r"(d) : "memory"); }
__device__ __forceinline__ float4 lds4f(uint32_t a) { float4 v; asm volatile("ld.shared.v4.f32 {%0,%1,%2,%3}, [%4];" : "=f"(v.x), "=f"(v.y), "=f"(v.z), "=f"(v.w) : "r"(a)); return v; }
__device__ __forceinline__ uint4 lds4u(uint32_t a) { uint4 v; asm volatile("ld.shared.v4.u32 {%0,%1,%2,%3}, [%4];" : "=r"(v.x), "=r"(v.y), "=r"(v.z), "=r"(v.w) : "r"(a) : "memory"); return v; }
__device__ __forceinline__ float2 lds2f(uint32_t a) { float2 v; asm volatile("ld.shared.v2.f32 {%0,%1}, [%2];" : "=f"(v.x), "=f"(v.y) : "r"(a)); return v; }
__device__ __forceinline__ void st_async4(uint32_t raddr, uint32_t a, uint32_t b, uint32_t c, uint32_t d, uint32_t rbar) {
  asm volatile("st.async.weak.shared::cluster.mbarrier::complete_tx::bytes.v4.b32 [%0], {%1,%2,%3,%4}, [%5];"
    :: "r"(raddr), "r"(a), "r"(b), "r"(c), "r"(d), "r"(rbar) : "memory");
}
__device__ __forceinline__ float wsum(float v) {
#pragma unroll
  for (int o = 16; o > 0; o >>= 1) v += __shfl_xor_sync(0xffffffffu, v, o);
  return v;
}
__device__ __forceinline__ float sum8(const uint4& v) {
  return ((bf_lo(v.x) + bf_hi(v.x)) + (bf_lo(v.y) + bf_hi(v.y))) + ((bf_lo(v.z) + bf_hi(v.z)) + (bf_lo(v.w) + bf_hi(v.w)));
}

struct Ctx {
  uint32_t sm;
  uint32_t da;
  uint32_t db;
  int lane;
};

template <int N, int TB>
__device__ __forceinline__ void mma_step(float (&acc)[N / 2], const Ctx& c, int st, uint32_t ph, int accum) {
  mbar_wait(c.sm + OFF_BAR + BAR_FULL + 8 * st, ph);
  const uint32_t a = c.da + st * (STB >> 4), b = c.db + st * (STB >> 4) + (TB ? (512u << 16) : (1u << 16));
  wg_fence();
  if constexpr (N == 128 && TB == 0) wgmma4_n128_tb0(acc, a, b, accum);
  if constexpr (N == 128 && TB == 1) wgmma4_n128_tb1(acc, a, b, accum);
  if constexpr (N == 96) wgmma4_n96_tb1(acc, a, b, accum);
  wg_commit();
}
__device__ __forceinline__ void release(const Ctx& c, int st) {
  if (c.lane == 0) mbar_arrive(c.sm + OFF_BAR + BAR_EMPTY + 8 * st);
}

template <int G>
__device__ __forceinline__ void epi_ab(const float (&acc)[64], const Ctx& c, float a0, float b0, float a1, float b1, __nv_bfloat16* p0) {
  uint32_t w0[4], w1[4];
#pragma unroll
  for (int i = 0; i < 4; i++) {
    float2 cs = lds2f(c.sm + OFF_VAB + (32 * G + 8 * i) * 4 + (c.lane & 3) * 8);
    const int r = 4 * (4 * G + i);
    w0[i] = pack2(fmaf(a0, acc[r], b0 * cs.x), fmaf(a0, acc[r + 1], b0 * cs.y));
    w1[i] = pack2(fmaf(a1, acc[r + 2], b1 * cs.x), fmaf(a1, acc[r + 3], b1 * cs.y));
  }
  stg4(p0 + 32 * G, w0[0], w0[1], w0[2], w0[3]);
  stg4(p0 + 32 * G + 8 * DM, w1[0], w1[1], w1[2], w1[3]);
}
template <int G, int VG, int NA>
__device__ __forceinline__ void epi_h(const float (&acc)[NA], const Ctx& c, float a0, float b0, float a1, float b1, __nv_bfloat16* p0) {
  uint32_t w0[4], w1[4];
#pragma unroll
  for (int i = 0; i < 4; i++) {
    float4 v = lds4f(c.sm + OFF_VH + (16 * VG + 4 * i) * 16 + (c.lane & 3) * 16);
    const int r = 4 * (4 * G + i);
    w0[i] = pack2(gelu_f(fmaf(a0, acc[r], fmaf(b0, v.x, v.z))), gelu_f(fmaf(a0, acc[r + 1], fmaf(b0, v.y, v.w))));
    w1[i] = pack2(gelu_f(fmaf(a1, acc[r + 2], fmaf(b1, v.x, v.z))), gelu_f(fmaf(a1, acc[r + 3], fmaf(b1, v.y, v.w))));
  }
  stg4(p0 + 32 * VG, w0[0], w0[1], w0[2], w0[3]);
  stg4(p0 + 32 * VG + 8 * FF, w1[0], w1[1], w1[2], w1[3]);
}
template <int G>
__device__ __forceinline__ void epi_g(const float (&acc)[64], const Ctx& c, uint32_t stg, uint4& o0, uint4& o1) {
  uint32_t w0[4], w1[4];
#pragma unroll
  for (int i = 0; i < 4; i++) {
    float2 b = lds2f(c.sm + OFF_B2 + (32 * G + 8 * i) * 4 + (c.lane & 3) * 8);
    const int r = 4 * (4 * G + i);
    w0[i] = pack2(silu_f(acc[r] + b.x), silu_f(acc[r + 1] + b.y));
    w1[i] = pack2(silu_f(acc[r + 2] + b.x), silu_f(acc[r + 3] + b.y));
  }
  const int r8 = c.lane & 7, mi = c.lane >> 3;
  const uint32_t wa = stg + r8 * 128 + ((((G & 1) * 4 + mi) ^ r8) << 4);
  __syncwarp();
  asm volatile("stmatrix.sync.aligned.m8n8.x4.shared.b16 [%0], {%1,%2,%3,%4};" :: "r"(wa), "r"(w0[0]), "r"(w0[1]), "r"(w0[2]), "r"(w0[3]) : "memory");
  asm volatile("stmatrix.sync.aligned.m8n8.x4.shared.b16 [%0], {%1,%2,%3,%4};" :: "r"(wa + 1024), "r"(w1[0]), "r"(w1[1]), "r"(w1[2]), "r"(w1[3]) : "memory");
  __syncwarp();
  const int rr = c.lane >> 2;
  const uint32_t ra = stg + rr * 128 + ((((G & 1) * 4 + (c.lane & 3)) ^ rr) << 4);
  o0 = lds4u(ra);
  o1 = lds4u(ra + 1024);
}

template <int ROLE>
__device__ __forceinline__ void tail(float (&y)[64], float (&m)[64], const Ctx& c, const Params& p, int tid, size_t ooff) {
  const uint32_t peer = ROLE ^ 1;
  uint4 g[4], xr[4];
  const uint32_t stg = c.sm + OFF_G + (tid >> 5) * 2048;
  const uint32_t rg = mapa(c.sm + OFF_G + tid * 16, peer), rgb = mapa(c.sm + OFF_BAR + BAR_G, peer);
#pragma unroll
  for (int s = NSTEPS - 6; s < NSTEPS; s++) {
    mma_step<128, 1>(y, c, s % NST, (s / NST) & 1, 1);
    wg_wait<1>();
    if (s == NSTEPS - 6) {
      release(c, (s - 1) % NST);
      asm volatile("barrier.cluster.wait.aligned;" ::: "memory");
      if (ROLE == 1) reg_fence(m);
    }
    if (s == NSTEPS - 5 && c.lane == 0) mbar_arrive_cluster(mapa(c.sm + OFF_BAR + BAR_OK, peer));
    if (ROLE == 1) {
      if (s == NSTEPS - 6) { uint4 t0, t1; epi_g<0>(m, c, stg, t0, t1); st_async4(rg, t0.x, t0.y, t0.z, t0.w, rgb); st_async4(rg + 4096, t1.x, t1.y, t1.z, t1.w, rgb); }
      if (s == NSTEPS - 5) { uint4 t0, t1; epi_g<1>(m, c, stg, t0, t1); st_async4(rg + 8192, t0.x, t0.y, t0.z, t0.w, rgb); st_async4(rg + 12288, t1.x, t1.y, t1.z, t1.w, rgb); }
      if (s == NSTEPS - 4) epi_g<2>(m, c, stg, g[0], g[1]);
      if (s == NSTEPS - 3) epi_g<3>(m, c, stg, g[2], g[3]);
    }
    if (s == NSTEPS - 3) {
      xr[0] = ldg_nc(p.x + ooff); xr[1] = ldg_nc(p.x + ooff + 8 * DM);
      xr[2] = ldg_nc(p.x + ooff + 32); xr[3] = ldg_nc(p.x + ooff + 8 * DM + 32);
    }
  }
  if (ROLE == 0) {
    mbar_wait(c.sm + OFF_BAR + BAR_G, 0);
#pragma unroll
    for (int v = 0; v < 4; v++) g[v] = lds4u(c.sm + OFF_G + v * 4096 + tid * 16);
  }
  mbar_wait(c.sm + OFF_BAR + BAR_OK, 0);
  const uint32_t rl = mapa(c.sm + LAND_STAGE * STB + tid * 16, peer), rlb = mapa(c.sm + OFF_BAR + BAR_Y, peer);
  wg_wait<0>();
  reg_fence(y);
  TLC(8);
  constexpr int SND = ROLE == 0 ? 32 : 0, KEEP = 32 - SND;
#pragma unroll
  for (int v = 0; v < 8; v++)
    st_async4(rl + v * 4096, __float_as_uint(y[SND + 4 * v]), __float_as_uint(y[SND + 4 * v + 1]), __float_as_uint(y[SND + 4 * v + 2]), __float_as_uint(y[SND + 4 * v + 3]), rlb);
  mbar_wait(c.sm + OFF_BAR + BAR_Y, 0);
  TLC(9);
#pragma unroll
  for (int G = 0; G < 2; G++) {
    float4 r[4];
#pragma unroll
    for (int i = 0; i < 4; i++) {
      uint4 t = lds4u(c.sm + LAND_STAGE * STB + (4 * G + i) * 4096 + tid * 16);
      r[i] = make_float4(__uint_as_float(t.x), __uint_as_float(t.y), __uint_as_float(t.z), __uint_as_float(t.w));
    }
    uint32_t o0[4], o1[4];
    const uint32_t g0[4] = {g[2 * G].x, g[2 * G].y, g[2 * G].z, g[2 * G].w}, g1[4] = {g[2 * G + 1].x, g[2 * G + 1].y, g[2 * G + 1].z, g[2 * G + 1].w};
    const uint32_t x0[4] = {xr[2 * G].x, xr[2 * G].y, xr[2 * G].z, xr[2 * G].w}, x1[4] = {xr[2 * G + 1].x, xr[2 * G + 1].y, xr[2 * G + 1].z, xr[2 * G + 1].w};
#pragma unroll
    for (int i = 0; i < 4; i++) {
      const int a = KEEP + 4 * (4 * G + i);
      o0[i] = pack2(fmaf(y[a] + r[i].x, bf_lo(g0[i]), bf_lo(x0[i])), fmaf(y[a + 1] + r[i].y, bf_hi(g0[i]), bf_hi(x0[i])));
      o1[i] = pack2(fmaf(y[a + 2] + r[i].z, bf_lo(g1[i]), bf_lo(x1[i])), fmaf(y[a + 3] + r[i].w, bf_hi(g1[i]), bf_hi(x1[i])));
    }
    stg4(p.out + ooff + 32 * G, o0[0], o0[1], o0[2], o0[3]);
    stg4(p.out + ooff + 32 * G + 8 * DM, o1[0], o1[1], o1[2], o1[3]);
  }
  TLC(10);
}

__global__ void __cluster_dims__(2, 1, 1) __launch_bounds__(384, 1) fused_kernel(const __grid_constant__ Params p) {
  extern __shared__ __align__(1024) uint8_t smem_raw[];
  const uint32_t sm = (uint32_t)__cvta_generic_to_shared(smem_raw);
  const int tid = threadIdx.x, lane = tid & 31;
  const int warp = __shfl_sync(0xffffffffu, tid >> 5, 0);
  const int role = blockIdx.x & 1, cb = (blockIdx.x >> 1) & 3, rb = blockIdx.x >> 3, j = blockIdx.x & 7;
  const uint32_t bars = sm + OFF_BAR;
  TLC(0);
  if (warp == 8) {
    if (elect_one()) {
      for (int s = 0; s < NST; s++) { mbar_init(bars + BAR_FULL + 8 * s, 1); mbar_init(bars + BAR_EMPTY + 8 * s, 8); }
      mbar_init(bars + BAR_VEC, 1); mbar_init(bars + BAR_G, 1); mbar_init(bars + BAR_Y, 1); mbar_init(bars + BAR_OK, 8);
      asm volatile("fence.mbarrier_init.release.cluster;" ::: "memory");
      asm volatile("fence.proxy.async.shared::cta;" ::: "memory");
      const CUtensorMap* md = j < 4 ? &p.mdre : &p.mdim;
      for (int k = 0; k < NST; k++) {
        mbar_expect_tx(bars + BAR_FULL + 8 * k, STB);
        tma2d(sm + k * STB, &p.mx, k * 64, rb * 128, bars + BAR_FULL + 8 * k);
        tma2d(sm + k * STB + 16384, md, k * 64, (j & 3) * 128, bars + BAR_FULL + 8 * k);
      }
      mbar_expect_tx(bars + BAR_G, 16384);
      mbar_expect_tx(bars + BAR_Y, 32768);
    }
    __syncwarp();
  }
  __syncthreads();
  asm volatile("barrier.cluster.arrive.relaxed.aligned;" ::: "memory");

  if (warp >= 8) {
    asm volatile("setmaxnreg.dec.sync.aligned.u32 120;");
    if (warp == 8) {
      if (elect_one()) {
        const unsigned epoch = (ld_rlx(&g_cnt[C_DONE]) >> 7) + 1;
        asm volatile("prefetch.tensormap [%0];" :: "l"(&p.mw1) : "memory");
        asm volatile("prefetch.tensormap [%0];" :: "l"(&p.mcr) : "memory");
        asm volatile("prefetch.tensormap [%0];" :: "l"(&p.mci) : "memory");
        asm volatile("prefetch.tensormap [%0];" :: "l"(&p.mab) : "memory");
        if (role) {
          asm volatile("prefetch.tensormap [%0];" :: "l"(&p.mh) : "memory");
          asm volatile("prefetch.tensormap [%0];" :: "l"(&p.mw2) : "memory");
        }
        int st = 0; uint32_t ph = 0;
        int pf = cb, pfc = 0;
        const int ny = role ? 18 : 46, y0 = role ? 46 : 0;
        const int row0 = rb * 128;
#define P_ACQ() mbar_wait(bars + BAR_EMPTY + 8 * st, ph); const uint32_t fb = bars + BAR_FULL + 8 * st, sa = sm + st * STB, sb = sa + 16384; mbar_expect_tx(fb, STB)
#define P_ADV() if (++st == NST) { st = 0; ph ^= 1; }
#define P_PF() if (pf < ny && ++pfc == 3) { pfc = 0; const int yy = y0 + pf; tma_pf2d(yy < 32 ? &p.mcr : &p.mci, (yy & 31) * 64, row0); pf += 4; }
        const CUtensorMap* md = j < 4 ? &p.mdre : &p.mdim;
        for (int k = NST; k < 8; k++) { P_ACQ(); tma2d(sa, &p.mx, k * 64, row0, fb); tma2d(sb, md, k * 64, (j & 3) * 128, fb); P_ADV(); P_PF(); }
        asm volatile("cp.async.bulk.prefetch.L2.global [%0], %1;" :: "l"(p.w2 + (size_t)blockIdx.x * (FF * DM / 128)), "r"(FF * DM / 128 * 2) : "memory");
        for (int k = 0; k < 16; k++) {
          P_ACQ(); tma2d(sa, &p.mx, (k & 7) * 64, row0, fb); tma3d(sb, &p.mw1, j * 224 + (k >> 3) * 96, (k & 7) * 64, 0, fb); P_ADV(); P_PF();
        }
        TLREC(11);
        if (!role) wait_cnt(&g_cnt[C_AB + cb * 32], 16 * epoch);
        wait_cnt(&g_cnt[C_AB + (4 + cb) * 32], 16 * epoch);
        asm volatile("fence.proxy.async.global;" ::: "memory");
        TLREC(12);
        const int nya = role ? 12 : 46;
        for (int k = y0; k < y0 + nya; k++) {
          P_ACQ(); tma2d(sa, k < 32 ? &p.mcr : &p.mci, (k & 31) * 64, row0, fb); tma3d(sb, &p.mab, 0, k * 64, cb * 2, fb); P_ADV(); P_PF();
        }
        if (role) {
          TLREC(13);
          wait_cnt(&g_cnt[C_H + rb * 32], 16 * epoch);
          asm volatile("fence.proxy.async.global;" ::: "memory");
          TLREC(14);
          for (int k = 0; k < 28; k++) {
            P_ACQ(); tma2d(sa, &p.mh, k * 64, row0, fb); tma5d(sb, &p.mw2, cb * 128, 2 * k, fb); tma5d(sb + 8192, &p.mw2, cb * 128 + 64, 2 * k, fb); P_ADV(); P_PF();
          }
          for (int k = 58; k < 64; k++) {
            P_ACQ(); tma2d(sa, &p.mci, (k & 31) * 64, row0, fb); tma3d(sb, &p.mab, 0, k * 64, cb * 2, fb); P_ADV();
          }
        }
        asm volatile("red.relaxed.gpu.global.add.u32 [%0], 1;" :: "l"(&g_cnt[C_DONE]) : "memory");
      }
    } else {
      unsigned epoch = 0;
      if (warp == 9) epoch = (ld_rlx(&g_cnt[C_DONE]) >> 7) + 1;
      if (warp < 11) {
        const int r0 = rb * 128 + j * 16 + (warp - 9) * 8;
        const int d0 = blockIdx.x * 8 + (warp - 9) * 4;
        const __nv_bfloat16* d = (d0 < DM ? p.dre + (size_t)d0 * DM : p.dim + (size_t)(d0 - DM) * DM) + lane * 8;
        uint4 v[8][2], u[4][2];
#pragma unroll
        for (int r = 0; r < 8; r++) { v[r][0] = ldg_nc(p.x + (size_t)(r0 + r) * DM + lane * 8); v[r][1] = ldg_nc(p.x + (size_t)(r0 + r) * DM + 256 + lane * 8); }
#pragma unroll
        for (int r = 0; r < 4; r++) { u[r][0] = ldg_nc(d + r * DM); u[r][1] = ldg_nc(d + r * DM + 256); }
        float mean = 0.f, var = 0.f;
#pragma unroll
        for (int r = 0; r < 8; r++) {
          const uint32_t w[8] = {v[r][0].x, v[r][0].y, v[r][0].z, v[r][0].w, v[r][1].x, v[r][1].y, v[r][1].z, v[r][1].w};
          const float mu = wsum(sum8(v[r][0]) + sum8(v[r][1])) * (1.0f / DM);
          float q = 0.f;
#pragma unroll
          for (int i = 0; i < 8; i++) { float a = bf_lo(w[i]) - mu, b = bf_hi(w[i]) - mu; q = fmaf(a, a, q); q = fmaf(b, b, q); }
          q = wsum(q) * (1.0f / DM);
          if (lane == r) { mean = mu; var = q; }
        }
        if (lane < 8) {
          const float m1 = bfr(mean), d1 = bfr(sqrtf(bfr(bfr(var) + 1e-5f))), i1 = 1.0f / d1;
          const float m2 = bfr((mean - m1) * i1), d2 = bfr(sqrtf(bfr(bfr(var * i1 * i1) + 1e-5f))), i2 = 1.0f / d2;
          g_stats[r0 + lane] = make_float4(i1, -m1 * i1, i1 * i2, -(m1 * i1 + m2) * i2);
        }
        float cs = 0.f;
#pragma unroll
        for (int r = 0; r < 4; r++) { const float t = wsum(sum8(u[r][0]) + sum8(u[r][1])); if (lane == r) cs = t; }
        if (lane < 4) g_cs[d0 + lane] = cs;
      } else if (blockIdx.x < 112) {
        const int c0 = blockIdx.x * 16 + (lane & 1) * 8;
        const __nv_bfloat16* w = p.w1 + (size_t)(lane >> 1) * FF + c0;
#pragma unroll
        for (int r = 16; r < 32; r++) asm volatile("prefetch.global.L2 [%0];" :: "l"(w + (size_t)r * 16 * FF));
        float s[8] = {0.f, 0.f, 0.f, 0.f, 0.f, 0.f, 0.f, 0.f};
#pragma unroll
        for (int h = 0; h < 2; h++) {
          uint4 v[16];
#pragma unroll
          for (int r = 0; r < 16; r++) v[r] = ldg_nc(w + (size_t)(h * 16 + r) * 16 * FF);
#pragma unroll
          for (int r = 0; r < 16; r++) {
            s[0] += bf_lo(v[r].x); s[1] += bf_hi(v[r].x); s[2] += bf_lo(v[r].y); s[3] += bf_hi(v[r].y);
            s[4] += bf_lo(v[r].z); s[5] += bf_hi(v[r].z); s[6] += bf_lo(v[r].w); s[7] += bf_hi(v[r].w);
          }
        }
#pragma unroll
        for (int o = 16; o > 1; o >>= 1) {
#pragma unroll
          for (int i = 0; i < 8; i++) s[i] += __shfl_xor_sync(0xffffffffu, s[i], o);
        }
        if (lane < 2) {
          *reinterpret_cast<float4*>(&g_cs[2 * DM + c0]) = make_float4(s[0], s[1], s[2], s[3]);
          *reinterpret_cast<float4*>(&g_cs[2 * DM + c0 + 4]) = make_float4(s[4], s[5], s[6], s[7]);
        }
      }
      if (warp != 9) {
        bar_arrive(4, 96);
      } else {
        bar_sync(4, 96);
        if (lane == 0) { red_rel(&g_cnt[C_PREP]); TLREC(15); wait_cnt(&g_cnt[C_PREP], 128 * epoch); }
        __syncwarp();
        const float sg = j < 4 ? 1.f : -1.f;
        float4 sv[4];
#pragma unroll
        for (int i = 0; i < 4; i++) sv[i] = __ldcg(&g_stats[rb * 128 + i * 32 + lane]);
        const float4 cab = __ldcg(reinterpret_cast<const float4*>(&g_cs[j * 128 + lane * 4]));
        float2 ch[4]; uint32_t bh[4];
#pragma unroll
        for (int i = 0; i < 4; i++) {
          const int pr = i * 32 + lane;
          if (pr < 112) { ch[i] = __ldcg(reinterpret_cast<const float2*>(&g_cs[2 * DM + j * 224 + pr * 2])); bh[i] = *reinterpret_cast<const uint32_t*>(p.b1 + j * 224 + pr * 2); }
        }
        const uint2 b2v = *reinterpret_cast<const uint2*>(p.b2 + cb * 128 + lane * 4);
        float4* s4 = reinterpret_cast<float4*>(smem_raw);
#pragma unroll
        for (int i = 0; i < 4; i++) s4[OFF_STATS / 16 + i * 32 + lane] = make_float4(sv[i].x * sg, sv[i].y * sg, sv[i].z, sv[i].w);
        s4[OFF_VAB / 16 + lane] = cab;
#pragma unroll
        for (int i = 0; i < 4; i++) { const int pr = i * 32 + lane; if (pr < 112) s4[OFF_VH / 16 + pr] = make_float4(ch[i].x, ch[i].y, bf_lo(bh[i]), bf_hi(bh[i])); }
        s4[OFF_B2 / 16 + lane] = make_float4(bf_lo(b2v.x), bf_hi(b2v.x), bf_lo(b2v.y), bf_hi(b2v.y));
        __syncwarp();
        if (lane == 0) { mbar_arrive(bars + BAR_VEC); TLREC(16); }
        bar_sync(1, 288);
        if (lane == 0) { red_rel(&g_cnt[C_AB + j * 32]); TLREC(17); }
        bar_sync(2, 288);
        if (lane == 0) red_rel(&g_cnt[C_H + rb * 32]);
        bar_sync(3, 288);
        if (lane == 0) { red_rel(&g_cnt[C_H + rb * 32]); TLREC(18); }
      }
    }
  } else {
    asm volatile("setmaxnreg.inc.sync.aligned.u32 192;");
    Ctx c; c.sm = sm; c.lane = lane;
    c.da = (((sm + (warp >> 2) * 8192) & 0x3FFFF) >> 4) | (1u << 16); c.db = ((sm + 16384) & 0x3FFFF) >> 4;
    const int rl = warp * 16 + (lane >> 2);
    const int q8 = (lane & 3) * 8;
    float P[64], Q[48], R[64], Y[64], M[64];
    {
      int st = 0; uint32_t ph = 0;
      for (int k = 0; k < 8; k++) {
        mma_step<128, 0>(P, c, st, ph, k);
        wg_wait<1>();
        if (k) release(c, st == 0 ? NST - 1 : st - 1);
        if (++st == NST) { st = 0; ph ^= 1; }
      }
    }
    TLC(2);
    float4 s0, s1;
    {
      __nv_bfloat16* pab = g_ab + (size_t)((j >> 2) * SEQ + rb * 128 + rl) * DM + (j & 3) * 128 + q8;
#pragma unroll
      for (int s = 8; s < 16; s++) {
        mma_step<96, 1>(Q, c, s % NST, (s / NST) & 1, s > 8);
        wg_wait<1>();
        release(c, (s - 1) % NST);
        if (s == 8) {
          reg_fence(P);
          mbar_wait(bars + BAR_VEC, 0);
          s0 = lds4f(sm + OFF_STATS + rl * 16); s1 = lds4f(sm + OFF_STATS + rl * 16 + 128);
          epi_ab<0>(P, c, s0.x, s0.y, s1.x, s1.y, pab);
        }
        if (s == 9) epi_ab<1>(P, c, s0.x, s0.y, s1.x, s1.y, pab);
        if (s == 10) epi_ab<2>(P, c, s0.x, s0.y, s1.x, s1.y, pab);
        if (s == 11) { epi_ab<3>(P, c, s0.x, s0.y, s1.x, s1.y, pab); bar_arrive(1, 288); }
      }
    }
    TLC(3);
    __nv_bfloat16* ph_ = g_h + (size_t)(rb * 128 + rl) * FF + j * 224 + q8;
#pragma unroll
    for (int s = 16; s < 24; s++) {
      mma_step<128, 1>(R, c, s % NST, (s / NST) & 1, s > 16);
      wg_wait<1>();
      release(c, (s - 1) % NST);
      if (s == 16) { reg_fence(Q); epi_h<0, 0>(Q, c, s0.z, s0.w, s1.z, s1.w, ph_); }
      if (s == 18) epi_h<1, 1>(Q, c, s0.z, s0.w, s1.z, s1.w, ph_);
      if (s == 20) { epi_h<2, 2>(Q, c, s0.z, s0.w, s1.z, s1.w, ph_); bar_arrive(2, 288); }
    }
    TLC(4);
#pragma unroll
    for (int s = 24; s < 30; s++) {
      mma_step<128, 1>(Y, c, s % NST, (s / NST) & 1, s > 24);
      wg_wait<1>();
      release(c, (s - 1) % NST);
      if (s == 24) { reg_fence(R); epi_h<0, 3>(R, c, s0.z, s0.w, s1.z, s1.w, ph_); }
      if (s == 25) epi_h<1, 4>(R, c, s0.z, s0.w, s1.z, s1.w, ph_);
      if (s == 26) epi_h<2, 5>(R, c, s0.z, s0.w, s1.z, s1.w, ph_);
      if (s == 27) { epi_h<3, 6>(R, c, s0.z, s0.w, s1.z, s1.w, ph_); bar_arrive(3, 288); }
    }
    TLC(5);
    int st = 30 % NST, pst = 29 % NST; uint32_t ph = (30 / NST) & 1;
    const int ny = role ? 6 : 34;
    for (int k = 0; k < ny; k++) {
      mma_step<128, 1>(Y, c, st, ph, 1);
      wg_wait<1>();
      release(c, pst);
      pst = st; if (++st == NST) { st = 0; ph ^= 1; }
    }
    TLC(6);
    const size_t ooff = (size_t)(rb * 128 + rl) * DM + cb * 128 + role * 64 + q8;
    if (role) {
      for (int k = 0; k < 28; k++) {
        mma_step<128, 1>(M, c, st, ph, k);
        wg_wait<1>();
        release(c, pst);
        pst = st; if (++st == NST) { st = 0; ph ^= 1; }
      }
      TLC(7);
      tail<1>(Y, M, c, p, tid, ooff);
    } else {
      TLC(7);
      tail<0>(Y, M, c, p, tid, ooff);
    }
  }
}

typedef CUresult (*EncFn)(CUtensorMap*, CUtensorMapDataType, cuuint32_t, void*, const cuuint64_t*, const cuuint64_t*, const cuuint32_t*,
                          const cuuint32_t*, CUtensorMapInterleave, CUtensorMapSwizzle, CUtensorMapL2promotion, CUtensorMapFloatOOBfill);

void make_map(EncFn enc, CUtensorMap* m, const void* ptr, int nd, const uint64_t* dims, const uint64_t* strides, const uint32_t* box) {
  const cuuint32_t es[5] = {1, 1, 1, 1, 1};
  cuuint64_t d[5], s[5]; cuuint32_t b[5];
  for (int i = 0; i < nd; i++) { d[i] = dims[i]; b[i] = box[i]; if (i + 1 < nd) s[i] = strides[i]; }
  enc(m, CU_TENSOR_MAP_DATA_TYPE_BFLOAT16, nd, const_cast<void*>(ptr), d, s, b, es, CU_TENSOR_MAP_INTERLEAVE_NONE,
      CU_TENSOR_MAP_SWIZZLE_128B, CU_TENSOR_MAP_L2_PROMOTION_L2_128B, CU_TENSOR_MAP_FLOAT_OOB_FILL_NONE);
}

}

extern "C" void kernel_launch(void* const* d_in, const int* in_sizes, int n_in, void* d_out, int out_size) {
  static Params prm;
  static const void* key[11];
  static EncFn enc = nullptr;
  bool same = enc != nullptr && key[10] == d_out;
  for (int i = 0; i < 10 && same; i++) same = key[i] == d_in[i];
  if (!same) {
    if (!enc) {
      cudaDriverEntryPointQueryResult q;
      cudaGetDriverEntryPoint("cuTensorMapEncodeTiled", reinterpret_cast<void**>(&enc), cudaEnableDefault, &q);
      cudaFuncSetAttribute(fused_kernel, cudaFuncAttributeMaxDynamicSharedMemorySize, SMEM_BYTES);
    }
    void *ab, *h;
    cudaGetSymbolAddress(&ab, g_ab);
    cudaGetSymbolAddress(&h, g_h);
    const uint32_t box2[2] = {64, 128}, box3[3] = {64, 64, 2}, box5[5] = {64, 2, 4, 4, 2};
    { const uint64_t d[2] = {DM, SEQ}, s[1] = {DM * 2}; make_map(enc, &prm.mx, d_in[0], 2, d, s, box2); }
    { const uint64_t d[2] = {SEQ, SEQ}, s[1] = {SEQ * 2}; make_map(enc, &prm.mcr, d_in[1], 2, d, s, box2); make_map(enc, &prm.mci, d_in[2], 2, d, s, box2); }
    { const uint64_t d[2] = {DM, DM}, s[1] = {DM * 2}; make_map(enc, &prm.mdre, d_in[3], 2, d, s, box2); make_map(enc, &prm.mdim, d_in[4], 2, d, s, box2); }
    { const uint64_t d[3] = {FF, DM, 2}, s[2] = {FF * 2, 128}; make_map(enc, &prm.mw1, d_in[6], 3, d, s, box3); }
    { const uint64_t d[3] = {64, 2 * SEQ, 8}, s[2] = {DM * 2, 128}; make_map(enc, &prm.mab, ab, 3, d, s, box3); }
    { const uint64_t d[2] = {FF, SEQ}, s[1] = {FF * 2}; make_map(enc, &prm.mh, h, 2, d, s, box2); }
    { const uint64_t d[5] = {DM, 2, 4, 4, FF / 32}, s[4] = {DM * 2, 8 * DM * 2, 2 * DM * 2, 32 * DM * 2}; make_map(enc, &prm.mw2, d_in[8], 5, d, s, box5); }
    prm.x = (const __nv_bfloat16*)d_in[0]; prm.dre = (const __nv_bfloat16*)d_in[3]; prm.dim = (const __nv_bfloat16*)d_in[4];
    prm.w1 = (const __nv_bfloat16*)d_in[6]; prm.b1 = (const __nv_bfloat16*)d_in[7]; prm.w2 = (const __nv_bfloat16*)d_in[8];
    prm.b2 = (const __nv_bfloat16*)d_in[9]; prm.out = (__nv_bfloat16*)d_out;
    for (int i = 0; i < 10; i++) key[i] = d_in[i];
    key[10] = d_out;
  }
  fused_kernel<<<128, 384, SMEM_BYTES>>>(prm);
}
```

```cpp
#include <cuda_runtime.h>
#include <cuda_bf16.h>
#include <cuda.h>
#include <stdint.h>

namespace {

constexpr int SEQ = 2048, DM = 512, FF = 1792;
constexpr int NST = 6;
constexpr int STB = 32768;
constexpr int OFF_STG = NST * STB;
constexpr int OFF_G = OFF_STG;
constexpr int OFF_VAB = OFF_STG + 32768;
constexpr int OFF_VH = OFF_VAB + 512;
constexpr int OFF_B2 = OFF_VH + 1792;
constexpr int OFF_BAR = OFF_B2 + 512;
constexpr int SMEM_BYTES = OFF_BAR + 256;
constexpr int BAR_FULL = 0, BAR_EMPTY = 48, BAR_V1 = 96, BAR_G = 104, BAR_Y = 112, BAR_OK = 120, BAR_V2 = 128, BAR_FREE = 136;
#define INIT_ST 6
constexpr int NSTEPS = 70;
constexpr int NYB = 6;
constexpr int LAND_STAGE = (NSTEPS - 6) % NST;

constexpr int C_DONE = 0, C_AB = 64, C_H = 64 + 8 * 32;

struct Params {
  CUtensorMap mx, mdre, mdim, mw1, mcr, mci, mab, mh, mw2, sab, sh;
  const __nv_bfloat16 *x, *dre, *dim, *w1, *b1, *w2, *b2;
  __nv_bfloat16* out;
};

__device__ __align__(1024) __nv_bfloat16 g_ab[2 * SEQ * DM];
__device__ __align__(1024) __nv_bfloat16 g_h[SEQ * FF];
__device__ float4 g_stats[SEQ];
__device__ __align__(16) float g_cs[2 * DM];
__device__ __align__(16) float g_csw[16 * FF];
__device__ unsigned g_cnt[64 + 8 * 32 + 16 * 32];
#define TLREC(ev) do {} while (0)
#define TLC(ev) do {} while (0)

__device__ __forceinline__ void mbar_init(uint32_t bar, uint32_t cnt) { asm volatile("mbarrier.init.shared::cta.b64 [%0], %1;" :: "r"(bar), "r"(cnt) : "memory"); }
__device__ __forceinline__ void mbar_expect_tx(uint32_t bar, uint32_t bytes) { asm volatile("mbarrier.arrive.expect_tx.shared::cta.b64 _, [%0], %1;" :: "r"(bar), "r"(bytes) : "memory"); }
__device__ __forceinline__ void mbar_arrive(uint32_t bar) { asm volatile("mbarrier.arrive.shared::cta.b64 _, [%0];" :: "r"(bar) : "memory"); }
__device__ __forceinline__ void mbar_arrive_cluster(uint32_t remote_bar) { asm volatile("mbarrier.arrive.shared::cluster.b64 _, [%0];" :: "r"(remote_bar) : "memory"); }
__device__ __forceinline__ uint32_t mapa(uint32_t addr, uint32_t cta) { uint32_t r; asm("mapa.shared::cluster.u32 %0, %1, %2;" : "=r"(r) : "r"(addr), "r"(cta)); return r; }
__device__ __forceinline__ bool mbar_try(uint32_t bar, uint32_t parity) {
  uint32_t ok;
  asm volatile("{\n.reg .pred p;\nmbarrier.try_wait.parity.shared::cta.b64 p, [%1], %2;\nselp.u32 %0, 1, 0, p;\n}" : "=r"(ok) : "r"(bar), "r"(parity) : "memory");
  return ok;
}
__device__ __forceinline__ void mbar_wait(uint32_t bar, uint32_t parity) {
  if (mbar_try(bar, parity)) return;
  uint32_t n = 0;
  while (!mbar_try(bar, parity)) { if (++n > (1u << 20)) __trap(); }
}
__device__ __forceinline__ bool elect_one() {
  uint32_t p;
  asm volatile("{\n.reg .pred p;\nelect.sync _|p, 0xffffffff;\nselp.u32 %0, 1, 0, p;\n}" : "=r"(p));
  return p;
}
__device__ __forceinline__ void tma2d(uint32_t dst, const CUtensorMap* m, int c0, int c1, uint32_t bar) {
  asm volatile("cp.async.bulk.tensor.2d.shared::cluster.global.mbarrier::complete_tx::bytes [%0], [%1, {%3, %4}], [%2];"
    :: "r"(dst), "l"(m), "r"(bar), "r"(c0), "r"(c1) : "memory");
}
__device__ __forceinline__ void tma3d(uint32_t dst, const CUtensorMap* m, int c0, int c1, int c2, uint32_t bar) {
  asm volatile("cp.async.bulk.tensor.3d.shared::cluster.global.mbarrier::complete_tx::bytes [%0], [%1, {%3, %4, %5}], [%2];"
    :: "r"(dst), "l"(m), "r"(bar), "r"(c0), "r"(c1), "r"(c2) : "memory");
}
__device__ __forceinline__ void tma5d(uint32_t dst, const CUtensorMap* m, int c0, int c4, uint32_t bar) {
  asm volatile("cp.async.bulk.tensor.5d.shared::cluster.global.mbarrier::complete_tx::bytes [%0], [%1, {%3, %5, %5, %5, %4}], [%2];"
    :: "r"(dst), "l"(m), "r"(bar), "r"(c0), "r"(c4), "r"(0) : "memory");
}
__device__ __forceinline__ void tma_pf2d(const CUtensorMap* m, int c0, int c1) {
  asm volatile("cp.async.bulk.prefetch.tensor.2d.L2.global [%0, {%1, %2}];" :: "l"(m), "r"(c0), "r"(c1) : "memory");
}
__device__ __forceinline__ void wg_fence() { asm volatile("wgmma.fence.sync.aligned;" ::: "memory"); }
__device__ __forceinline__ void wg_commit() { asm volatile("wgmma.commit_group.sync.aligned;" ::: "memory"); }
template <int N> __device__ __forceinline__ void wg_wait() { asm volatile("wgmma.wait_group.sync.aligned %0;" :: "n"(N) : "memory"); }
template <int N> __device__ __forceinline__ void reg_fence(float (&d)[N]) {
#pragma unroll
  for (int i = 0; i < N; i++) asm volatile("" : "+f"(d[i]) :: "memory");
}
__device__ __forceinline__ void wgmma4_n128_tb0(float (&d)[64], uint32_t a, uint32_t b, int scale_d) {
  asm volatile("{\n.reg .pred p;\n.reg .b32 la, lb, hi;\n.reg .b64 da, db;\nsetp.ne.b32 p, %66, 0;\nmov.b32 hi, 0x40000040;\n"
    "add.u32 la, %64, 0;\nadd.u32 lb, %65, 0;\nmov.b64 da, {la, hi};\nmov.b64 db, {lb, hi};\n"
    "wgmma.mma_async.sync.aligned.m64n128k16.f32.bf16.bf16 "
    "{%0, %1, %2, %3, %4, %5, %6, %7, %8, %9, %10, %11, %12, %13, %14, %15, %16, %17, %18, %19, %20, %21, %22, %23, %24, %25, %26, %27, %28, %29, %30, %31, %32, %33, %34, %35, %36, %37, %38, %39, %40, %41, %42, %43, %44, %45, %46, %47, %48, %49, %50, %51, %52, %53, %54, %55, %56, %57, %58, %59, %60, %61, %62, %63}, "
    "da, db, p, 1, 1, 0, 0;\n"
    "add.u32 la, %64, 2;\nadd.u32 lb, %65, 2;\nmov.b64 da, {la, hi};\nmov.b64 db, {lb, hi};\n"
    "wgmma.mma_async.sync.aligned.m64n128k16.f32.bf16.bf16 "
    "{%0, %1, %2, %3, %4, %5, %6, %7, %8, %9, %10, %11, %12, %13, %14, %15, %16, %17, %18, %19, %20, %21, %22, %23, %24, %25, %26, %27, %28, %29, %30, %31, %32, %33, %34, %35, %36, %37, %38, %39, %40, %41, %42, %43, %44, %45, %46, %47, %48, %49, %50, %51, %52, %53, %54, %55, %56, %57, %58, %59, %60, %61, %62, %63}, "
    "da, db, 1, 1, 1, 0, 0;\n"
    "add.u32 la, %64, 4;\nadd.u32 lb, %65, 4;\nmov.b64 da, {la, hi};\nmov.b64 db, {lb, hi};\n"
    "wgmma.mma_async.sync.aligned.m64n128k16.f32.bf16.bf16 "
    "{%0, %1, %2, %3, %4, %5, %6, %7, %8, %9, %10, %11, %12, %13, %14, %15, %16, %17, %18, %19, %20, %21, %22, %23, %24, %25, %26, %27, %28, %29, %30, %31, %32, %33, %34, %35, %36, %37, %38, %39, %40, %41, %42, %43, %44, %45, %46, %47, %48, %49, %50, %51, %52, %53, %54, %55, %56, %57, %58, %59, %60, %61, %62, %63}, "
    "da, db, 1, 1, 1, 0, 0;\n"
    "add.u32 la, %64, 6;\nadd.u32 lb, %65, 6;\nmov.b64 da, {la, hi};\nmov.b64 db, {lb, hi};\n"
    "wgmma.mma_async.sync.aligned.m64n128k16.f32.bf16.bf16 "
    "{%0, %1, %2, %3, %4, %5, %6, %7, %8, %9, %10, %11, %12, %13, %14, %15, %16, %17, %18, %19, %20, %21, %22, %23, %24, %25, %26, %27, %28, %29, %30, %31, %32, %33, %34, %35, %36, %37, %38, %39, %40, %41, %42, %43, %44, %45, %46, %47, %48, %49, %50, %51, %52, %53, %54, %55, %56, %57, %58, %59, %60, %61, %62, %63}, "
    "da, db, 1, 1, 1, 0, 0;\n"
    "}\n"
    : "+f"(d[0]), "+f"(d[1]), "+f"(d[2]), "+f"(d[3]), "+f"(d[4]), "+f"(d[5]), "+f"(d[6]), "+f"(d[7]), "+f"(d[8]), "+f"(d[9]), "+f"(d[10]), "+f"(d[11]), "+f"(d[12]), "+f"(d[13]), "+f"(d[14]), "+f"(d[15]), "+f"(d[16]), "+f"(d[17]), "+f"(d[18]), "+f"(d[19]), "+f"(d[20]), "+f"(d[21]), "+f"(d[22]), "+f"(d[23]), "+f"(d[24]), "+f"(d[25]), "+f"(d[26]), "+f"(d[27]), "+f"(d[28]), "+f"(d[29]), "+f"(d[30]), "+f"(d[31]), "+f"(d[32]), "+f"(d[33]), "+f"(d[34]), "+f"(d[35]), "+f"(d[36]), "+f"(d[37]), "+f"(d[38]), "+f"(d[39]), "+f"(d[40]), "+f"(d[41]), "+f"(d[42]), "+f"(d[43]), "+f"(d[44]), "+f"(d[45]), "+f"(d[46]), "+f"(d[47]), "+f"(d[48]), "+f"(d[49]), "+f"(d[50]), "+f"(d[51]), "+f"(d[52]), "+f"(d[53]), "+f"(d[54]), "+f"(d[55]), "+f"(d[56]), "+f"(d[57]), "+f"(d[58]), "+f"(d[59]), "+f"(d[60]), "+f"(d[61]), "+f"(d[62]), "+f"(d[63])
    : "r"(a), "r"(b), "r"(scale_d));
}
__device__ __forceinline__ void wgmma4_n128_tb1(float (&d)[64], uint32_t a, uint32_t b, int scale_d) {
  asm volatile("{\n.reg .pred p;\n.reg .b32 la, lb, hi;\n.reg .b64 da, db;\nsetp.ne.b32 p, %66, 0;\nmov.b32 hi, 0x40000040;\n"
    "add.u32 la, %64, 0;\nadd.u32 lb, %65, 0;\nmov.b64 da, {la, hi};\nmov.b64 db, {lb, hi};\n"
    "wgmma.mma_async.sync.aligned.m64n128k16.f32.bf16.bf16 "
    "{%0, %1, %2, %3, %4, %5, %6, %7, %8, %9, %10, %11, %12, %13, %14, %15, %16, %17, %18, %19, %20, %21, %22, %23, %24, %25, %26, %27, %28, %29, %30, %31, %32, %33, %34, %35, %36, %37, %38, %39, %40, %41, %42, %43, %44, %45, %46, %47, %48, %49, %50, %51, %52, %53, %54, %55, %56, %57, %58, %59, %60, %61, %62, %63}, "
    "da, db, p, 1, 1, 0, 1;\n"
    "add.u32 la, %64, 2;\nadd.u32 lb, %65, 128;\nmov.b64 da, {la, hi};\nmov.b64 db, {lb, hi};\n"
    "wgmma.mma_async.sync.aligned.m64n128k16.f32.bf16.bf16 "
    "{%0, %1, %2, %3, %4, %5, %6, %7, %8, %9, %10, %11, %12, %13, %14, %15, %16, %17, %18, %19, %20, %21, %22, %23, %24, %25, %26, %27, %28, %29, %30, %31, %32, %33, %34, %35, %36, %37, %38, %39, %40, %41, %42, %43, %44, %45, %46, %47, %48, %49, %50, %51, %52, %53, %54, %55, %56, %57, %58, %59, %60, %61, %62, %63}, "
    "da, db, 1, 1, 1, 0, 1;\n"
    "add.u32 la, %64, 4;\nadd.u32 lb, %65, 256;\nmov.b64 da, {la, hi};\nmov.b64 db, {lb, hi};\n"
    "wgmma.mma_async.sync.aligned.m64n128k16.f32.bf16.bf16 "
    "{%0, %1, %2, %3, %4, %5, %6, %7, %8, %9, %10, %11, %12, %13, %14, %15, %16, %17, %18, %19, %20, %21, %22, %23, %24, %25, %26, %27, %28, %29, %30, %31, %32, %33, %34, %35, %36, %37, %38, %39, %40, %41, %42, %43, %44, %45, %46, %47, %48, %49, %50, %51, %52, %53, %54, %55, %56, %57, %58, %59, %60, %61, %62, %63}, "
    "da, db, 1, 1, 1, 0, 1;\n"
    "add.u32 la, %64, 6;\nadd.u32 lb, %65, 384;\nmov.b64 da, {la, hi};\nmov.b64 db, {lb, hi};\n"
    "wgmma.mma_async.sync.aligned.m64n128k16.f32.bf16.bf16 "
    "{%0, %1, %2, %3, %4, %5, %6, %7, %8, %9, %10, %11, %12, %13, %14, %15, %16, %17, %18, %19, %20, %21, %22, %23, %24, %25, %26, %27, %28, %29, %30, %31, %32, %33, %34, %35, %36, %37, %38, %39, %40, %41, %42, %43, %44, %45, %46, %47, %48, %49, %50, %51, %52, %53, %54, %55, %56, %57, %58, %59, %60, %61, %62, %63}, "
    "da, db, 1, 1, 1, 0, 1;\n"
    "}\n"
    : "+f"(d[0]), "+f"(d[1]), "+f"(d[2]), "+f"(d[3]), "+f"(d[4]), "+f"(d[5]), "+f"(d[6]), "+f"(d[7]), "+f"(d[8]), "+f"(d[9]), "+f"(d[10]), "+f"(d[11]), "+f"(d[12]), "+f"(d[13]), "+f"(d[14]), "+f"(d[15]), "+f"(d[16]), "+f"(d[17]), "+f"(d[18]), "+f"(d[19]), "+f"(d[20]), "+f"(d[21]), "+f"(d[22]), "+f"(d[23]), "+f"(d[24]), "+f"(d[25]), "+f"(d[26]), "+f"(d[27]), "+f"(d[28]), "+f"(d[29]), "+f"(d[30]), "+f"(d[31]), "+f"(d[32]), "+f"(d[33]), "+f"(d[34]), "+f"(d[35]), "+f"(d[36]), "+f"(d[37]), "+f"(d[38]), "+f"(d[39]), "+f"(d[40]), "+f"(d[41]), "+f"(d[42]), "+f"(d[43]), "+f"(d[44]), "+f"(d[45]), "+f"(d[46]), "+f"(d[47]), "+f"(d[48]), "+f"(d[49]), "+f"(d[50]), "+f"(d[51]), "+f"(d[52]), "+f"(d[53]), "+f"(d[54]), "+f"(d[55]), "+f"(d[56]), "+f"(d[57]), "+f"(d[58]), "+f"(d[59]), "+f"(d[60]), "+f"(d[61]), "+f"(d[62]), "+f"(d[63])
    : "r"(a), "r"(b), "r"(scale_d));
}
__device__ __forceinline__ void wgmma4_n96_tb1(float (&d)[48], uint32_t a, uint32_t b, int scale_d) {
  asm volatile("{\n.reg .pred p;\n.reg .b32 la, lb, hi;\n.reg .b64 da, db;\nsetp.ne.b32 p, %50, 0;\nmov.b32 hi, 0x40000040;\n"
    "add.u32 la, %48, 0;\nadd.u32 lb, %49, 0;\nmov.b64 da, {la, hi};\nmov.b64 db, {lb, hi};\n"
    "wgmma.mma_async.sync.aligned.m64n96k16.f32.bf16.bf16 "
    "{%0, %1, %2, %3, %4, %5, %6, %7, %8, %9, %10, %11, %12, %13, %14, %15, %16, %17, %18, %19, %20, %21, %22, %23, %24, %25, %26, %27, %28, %29, %30, %31, %32, %33, %34, %35, %36, %37, %38, %39, %40, %41, %42, %43, %44, %45, %46, %47}, "
    "da, db, p, 1, 1, 0, 1;\n"
    "add.u32 la, %48, 2;\nadd.u32 lb, %49, 128;\nmov.b64 da, {la, hi};\nmov.b64 db, {lb, hi};\n"
    "wgmma.mma_async.sync.aligned.m64n96k16.f32.bf16.bf16 "
    "{%0, %1, %2, %3, %4, %5, %6, %7, %8, %9, %10, %11, %12, %13, %14, %15, %16, %17, %18, %19, %20, %21, %22, %23, %24, %25, %26, %27, %28, %29, %30, %31, %32, %33, %34, %35, %36, %37, %38, %39, %40, %41, %42, %43, %44, %45, %46, %47}, "
    "da, db, 1, 1, 1, 0, 1;\n"
    "add.u32 la, %48, 4;\nadd.u32 lb, %49, 256;\nmov.b64 da, {la, hi};\nmov.b64 db, {lb, hi};\n"
    "wgmma.mma_async.sync.aligned.m64n96k16.f32.bf16.bf16 "
    "{%0, %1, %2, %3, %4, %5, %6, %7, %8, %9, %10, %11, %12, %13, %14, %15, %16, %17, %18, %19, %20, %21, %22, %23, %24, %25, %26, %27, %28, %29, %30, %31, %32, %33, %34, %35, %36, %37, %38, %39, %40, %41, %42, %43, %44, %45, %46, %47}, "
    "da, db, 1, 1, 1, 0, 1;\n"
    "add.u32 la, %48, 6;\nadd.u32 lb, %49, 384;\nmov.b64 da, {la, hi};\nmov.b64 db, {lb, hi};\n"
    "wgmma.mma_async.sync.aligned.m64n96k16.f32.bf16.bf16 "
    "{%0, %1, %2, %3, %4, %5, %6, %7, %8, %9, %10, %11, %12, %13, %14, %15, %16, %17, %18, %19, %20, %21, %22, %23, %24, %25, %26, %27, %28, %29, %30, %31, %32, %33, %34, %35, %36, %37, %38, %39, %40, %41, %42, %43, %44, %45, %46, %47}, "
    "da, db, 1, 1, 1, 0, 1;\n"
    "}\n"
    : "+f"(d[0]), "+f"(d[1]), "+f"(d[2]), "+f"(d[3]), "+f"(d[4]), "+f"(d[5]), "+f"(d[6]), "+f"(d[7]), "+f"(d[8]), "+f"(d[9]), "+f"(d[10]), "+f"(d[11]), "+f"(d[12]), "+f"(d[13]), "+f"(d[14]), "+f"(d[15]), "+f"(d[16]), "+f"(d[17]), "+f"(d[18]), "+f"(d[19]), "+f"(d[20]), "+f"(d[21]), "+f"(d[22]), "+f"(d[23]), "+f"(d[24]), "+f"(d[25]), "+f"(d[26]), "+f"(d[27]), "+f"(d[28]), "+f"(d[29]), "+f"(d[30]), "+f"(d[31]), "+f"(d[32]), "+f"(d[33]), "+f"(d[34]), "+f"(d[35]), "+f"(d[36]), "+f"(d[37]), "+f"(d[38]), "+f"(d[39]), "+f"(d[40]), "+f"(d[41]), "+f"(d[42]), "+f"(d[43]), "+f"(d[44]), "+f"(d[45]), "+f"(d[46]), "+f"(d[47])
    : "r"(a), "r"(b), "r"(scale_d));
}

__device__ __forceinline__ void bar_arrive(int id, int n) { asm volatile("bar.arrive %0, %1;" :: "r"(id), "r"(n) : "memory"); }
__device__ __forceinline__ void bar_sync(int id, int n) { asm volatile("bar.sync %0, %1;" :: "r"(id), "r"(n) : "memory"); }
__device__ __forceinline__ unsigned ld_rlx(const unsigned* p) { unsigned v; asm volatile("ld.relaxed.gpu.global.u32 %0, [%1];" : "=r"(v) : "l"(p) : "memory"); return v; }
__device__ __forceinline__ void red_add(unsigned* p) { asm volatile("red.relaxed.gpu.global.add.u32 [%0], 1;" :: "l"(p) : "memory"); }
__device__ __forceinline__ void wait_cnt(const unsigned* p, unsigned target) {
  uint32_t n = 0;
  while ((int)(ld_rlx(p) - target) < 0) { if (++n > (1u << 20)) __trap(); }
}
__device__ __forceinline__ float bf_lo(uint32_t v) { return __uint_as_float(v << 16); }
__device__ __forceinline__ float bf_hi(uint32_t v) { return __uint_as_float(v & 0xffff0000u); }
__device__ __forceinline__ uint32_t pack2(float lo, float hi) { uint32_t r; asm("cvt.rn.bf16x2.f32 %0, %1, %2;" : "=r"(r) : "f"(hi), "f"(lo)); return r; }
__device__ __forceinline__ float bfr(float v) { return __bfloat162float(__float2bfloat16_rn(v)); }
__device__ __forceinline__ float gelu_f(float t) {
  const float k0 = 0.7978845608028654f, k1 = k0 * 0.044715f;
  float th; asm("tanh.approx.f32 %0, %1;" : "=f"(th) : "f"(t * fmaf(t * t, k1, k0)));
  const float hf = 0.5f * t;
  return fmaf(hf, th, hf);
}
__device__ __forceinline__ float silu_f(float z) {
  const float hz = 0.5f * z;
  float th; asm("tanh.approx.f32 %0, %1;" : "=f"(th) : "f"(hz));
  return fmaf(hz, th, hz);
}
__device__ __forceinline__ uint32_t tagf(float v, uint32_t tag) { return (__float_as_uint(v) & ~3u) | tag; }
__device__ __forceinline__ uint4 ld_msg(const void* p) { uint4 v; asm volatile("ld.relaxed.gpu.global.v4.u32 {%0,%1,%2,%3}, [%4];" : "=r"(v.x), "=r"(v.y), "=r"(v.z), "=r"(v.w) : "l"(p) : "memory"); return v; }
__device__ __forceinline__ void st_msg(void* p, uint32_t a, uint32_t b, uint32_t c, uint32_t d) { asm volatile("st.relaxed.gpu.global.v4.u32 [%0], {%1,%2,%3,%4};" :: "l"(p), "r"(a), "r"(b), "r"(c), "r"(d) : "memory"); }
__device__ __forceinline__ uint32_t stale(const uint4& v, uint32_t tag) { return ((v.x ^ tag) | (v.y ^ tag) | (v.z ^ tag) | (v.w ^ tag)) & 3u; }
__device__ __forceinline__ void sts4(uint32_t a, uint32_t x, uint32_t y, uint32_t z, uint32_t w) { asm volatile("st.shared.v4.u32 [%0], {%1,%2,%3,%4};" :: "r"(a), "r"(x), "r"(y), "r"(z), "r"(w) : "memory"); }
__device__ __forceinline__ void tma_st2d(const CUtensorMap* m, uint32_t src, int c0, int c1) {
  asm volatile("cp.async.bulk.tensor.2d.global.shared::cta.bulk_group [%0, {%2, %3}], [%1];" :: "l"(m), "r"(src), "r"(c0), "r"(c1) : "memory");
}
__device__ __forceinline__ void fence_async_smem() { asm volatile("fence.proxy.async.shared::cta;" ::: "memory"); }
__device__ __forceinline__ uint4 ldg_nc(const void* p) { uint4 v; asm volatile("ld.global.nc.v4.u32 {%0,%1,%2,%3}, [%4];" : "=r"(v.x), "=r"(v.y), "=r"(v.z), "=r"(v.w) : "l"(p)); return v; }
__device__ __forceinline__ void stg4(void* p, uint32_t a, uint32_t b, uint32_t c, uint32_t d) { asm volatile("st.global.v4.u32 [%0], {%1,%2,%3,%4};" :: "l"(p), "r"(a), "r"(b), "r"(c), "r"(d) : "memory"); }
__device__ __forceinline__ float4 lds4f(uint32_t a) { float4 v; asm volatile("ld.shared.v4.f32 {%0,%1,%2,%3}, [%4];" : "=f"(v.x), "=f"(v.y), "=f"(v.z), "=f"(v.w) : "r"(a)); return v; }
__device__ __forceinline__ uint4 lds4u(uint32_t a) { uint4 v; asm volatile("ld.shared.v4.u32 {%0,%1,%2,%3}, [%4];" : "=r"(v.x), "=r"(v.y), "=r"(v.z), "=r"(v.w) : "r"(a) : "memory"); return v; }
__device__ __forceinline__ float2 lds2f(uint32_t a) { float2 v; asm volatile("ld.shared.v2.f32 {%0,%1}, [%2];" : "=f"(v.x), "=f"(v.y) : "r"(a)); return v; }
__device__ __forceinline__ void st_async4(uint32_t raddr, uint32_t a, uint32_t b, uint32_t c, uint32_t d, uint32_t rbar) {
  asm volatile("st.async.weak.shared::cluster.mbarrier::complete_tx::bytes.v4.b32 [%0], {%1,%2,%3,%4}, [%5];"
    :: "r"(raddr), "r"(a), "r"(b), "r"(c), "r"(d), "r"(rbar) : "memory");
}
__device__ __forceinline__ float wsum(float v) {
#pragma unroll
  for (int o = 16; o > 0; o >>= 1) v += __shfl_xor_sync(0xffffffffu, v, o);
  return v;
}
__device__ __forceinline__ float sum8(const uint4& v) {
  return ((bf_lo(v.x) + bf_hi(v.x)) + (bf_lo(v.y) + bf_hi(v.y))) + ((bf_lo(v.z) + bf_hi(v.z)) + (bf_lo(v.w) + bf_hi(v.w)));
}

struct Ctx {
  uint32_t sm;
  uint32_t da;
  uint32_t db;
  int lane;
};

template <int N, int TB>
__device__ __forceinline__ void mma_step(float (&acc)[N / 2], const Ctx& c, int st, uint32_t ph, int accum) {
  mbar_wait(c.sm + OFF_BAR + BAR_FULL + 8 * st, ph);
  const uint32_t a = c.da + st * (STB >> 4), b = c.db + st * (STB >> 4) + (TB ? (512u << 16) : (1u << 16));
  wg_fence();
  if constexpr (N == 128 && TB == 0) wgmma4_n128_tb0(acc, a, b, accum);
  if constexpr (N == 128 && TB == 1) wgmma4_n128_tb1(acc, a, b, accum);
  if constexpr (N == 96) wgmma4_n96_tb1(acc, a, b, accum);
  wg_commit();
}
__device__ __forceinline__ void release(const Ctx& c, int st) {
  if (c.lane == 0) mbar_arrive(c.sm + OFF_BAR + BAR_EMPTY + 8 * st);
}

template <int G>
__device__ __forceinline__ void epi_ab(const float (&acc)[64], const Ctx& c, float a0, float b0, float a1, float b1, uint32_t stg) {
  uint32_t w0[4], w1[4];
#pragma unroll
  for (int i = 0; i < 4; i++) {
    float2 cs = lds2f(c.sm + OFF_VAB + (32 * G + 8 * i) * 4 + (c.lane & 3) * 8);
    const int r = 4 * (4 * G + i);
    w0[i] = pack2(fmaf(a0, acc[r], b0 * cs.x), fmaf(a0, acc[r + 1], b0 * cs.y));
    w1[i] = pack2(fmaf(a1, acc[r + 2], b1 * cs.x), fmaf(a1, acc[r + 3], b1 * cs.y));
  }
  sts4(stg + G * 8192, w0[0], w0[1], w0[2], w0[3]);
  sts4(stg + G * 8192 + 512, w1[0], w1[1], w1[2], w1[3]);
}
template <int G, int VG, int NA>
__device__ __forceinline__ void epi_h(const float (&acc)[NA], const Ctx& c, float a0, float b0, float a1, float b1, uint32_t stg) {
  uint32_t w0[4], w1[4];
#pragma unroll
  for (int i = 0; i < 4; i++) {
    float4 v = lds4f(c.sm + OFF_VH + (16 * VG + 4 * i) * 16 + (c.lane & 3) * 16);
    const int r = 4 * (4 * G + i);
    w0[i] = pack2(gelu_f(fmaf(a0, acc[r], fmaf(b0, v.x, v.z))), gelu_f(fmaf(a0, acc[r + 1], fmaf(b0, v.y, v.w))));
    w1[i] = pack2(gelu_f(fmaf(a1, acc[r + 2], fmaf(b1, v.x, v.z))), gelu_f(fmaf(a1, acc[r + 3], fmaf(b1, v.y, v.w))));
  }
  sts4(stg + G * 8192, w0[0], w0[1], w0[2], w0[3]);
  sts4(stg + G * 8192 + 512, w1[0], w1[1], w1[2], w1[3]);
}
template <int G>
__device__ __forceinline__ void epi_g(const float (&acc)[64], const Ctx& c, uint32_t stg, uint4& o0, uint4& o1) {
  uint32_t w0[4], w1[4];
#pragma unroll
  for (int i = 0; i < 4; i++) {
    float2 b = lds2f(c.sm + OFF_B2 + (32 * G + 8 * i) * 4 + (c.lane & 3) * 8);
    const int r = 4 * (4 * G + i);
    w0[i] = pack2(silu_f(acc[r] + b.x), silu_f(acc[r + 1] + b.y));
    w1[i] = pack2(silu_f(acc[r + 2] + b.x), silu_f(acc[r + 3] + b.y));
  }
  const int r8 = c.lane & 7, mi = c.lane >> 3;
  const uint32_t wa = stg + r8 * 128 + ((((G & 1) * 4 + mi) ^ r8) << 4);
  __syncwarp();
  asm volatile("stmatrix.sync.aligned.m8n8.x4.shared.b16 [%0], {%1,%2,%3,%4};" :: "r"(wa), "r"(w0[0]), "r"(w0[1]), "r"(w0[2]), "r"(w0[3]) : "memory");
  asm volatile("stmatrix.sync.aligned.m8n8.x4.shared.b16 [%0], {%1,%2,%3,%4};" :: "r"(wa + 1024), "r"(w1[0]), "r"(w1[1]), "r"(w1[2]), "r"(w1[3]) : "memory");
  __syncwarp();
  const int rr = c.lane >> 2;
  const uint32_t ra = stg + rr * 128 + ((((G & 1) * 4 + (c.lane & 3)) ^ rr) << 4);
  o0 = lds4u(ra);
  o1 = lds4u(ra + 1024);
}

template <int ROLE>
__device__ __forceinline__ void tail(float (&y)[64], float (&m)[64], const Ctx& c, const Params& p, int tid, size_t ooff) {
  const uint32_t peer = ROLE ^ 1;
  uint4 g[4], xr[4];
  const uint32_t stg = c.sm + OFF_G + (tid >> 5) * 2048;
  const uint32_t rg = mapa(c.sm + OFF_G + tid * 16, peer), rgb = mapa(c.sm + OFF_BAR + BAR_G, peer);
#pragma unroll
  for (int s = NSTEPS - 6; s < NSTEPS; s++) {
    mma_step<128, 1>(y, c, s % NST, (s / NST) & 1, 1);
    wg_wait<1>();
    if (s == NSTEPS - 6) {
      release(c, (s - 1) % NST);
      asm volatile("barrier.cluster.wait.aligned;" ::: "memory");
      if (ROLE == 1) reg_fence(m);
    }
    if (s == NSTEPS - 5 && c.lane == 0) mbar_arrive_cluster(mapa(c.sm + OFF_BAR + BAR_OK, peer));
    if (ROLE == 1) {
      if (s == NSTEPS - 6) { uint4 t0, t1; epi_g<0>(m, c, stg, t0, t1); st_async4(rg, t0.x, t0.y, t0.z, t0.w, rgb); st_async4(rg + 4096, t1.x, t1.y, t1.z, t1.w, rgb); }
      if (s == NSTEPS - 5) { uint4 t0, t1; epi_g<1>(m, c, stg, t0, t1); st_async4(rg + 8192, t0.x, t0.y, t0.z, t0.w, rgb); st_async4(rg + 12288, t1.x, t1.y, t1.z, t1.w, rgb); }
      if (s == NSTEPS - 4) epi_g<2>(m, c, stg, g[0], g[1]);
      if (s == NSTEPS - 3) epi_g<3>(m, c, stg, g[2], g[3]);
    }
    if (s == NSTEPS - 3) {
      xr[0] = ldg_nc(p.x + ooff); xr[1] = ldg_nc(p.x + ooff + 8 * DM);
      xr[2] = ldg_nc(p.x + ooff + 32); xr[3] = ldg_nc(p.x + ooff + 8 * DM + 32);
    }
  }
  if (ROLE == 0) {
    mbar_wait(c.sm + OFF_BAR + BAR_G, 0);
#pragma unroll
    for (int v = 0; v < 4; v++) g[v] = lds4u(c.sm + OFF_G + v * 4096 + tid * 16);
  }
  mbar_wait(c.sm + OFF_BAR + BAR_OK, 0);
  const uint32_t rl = mapa(c.sm + LAND_STAGE * STB + tid * 16, peer), rlb = mapa(c.sm + OFF_BAR + BAR_Y, peer);
  wg_wait<0>();
  reg_fence(y);
  TLC(8);
  constexpr int SND = ROLE == 0 ? 32 : 0, KEEP = 32 - SND;
#pragma unroll
  for (int v = 0; v < 8; v++)
    st_async4(rl + v * 4096, __float_as_uint(y[SND + 4 * v]), __float_as_uint(y[SND + 4 * v + 1]), __float_as_uint(y[SND + 4 * v + 2]), __float_as_uint(y[SND + 4 * v + 3]), rlb);
  mbar_wait(c.sm + OFF_BAR + BAR_Y, 0);
  TLC(9);
#pragma unroll
  for (int G = 0; G < 2; G++) {
    float4 r[4];
#pragma unroll
    for (int i = 0; i < 4; i++) {
      uint4 t = lds4u(c.sm + LAND_STAGE * STB + (4 * G + i) * 4096 + tid * 16);
      r[i] = make_float4(__uint_as_float(t.x), __uint_as_float(t.y), __uint_as_float(t.z), __uint_as_float(t.w));
    }
    uint32_t o0[4], o1[4];
    const uint32_t g0[4] = {g[2 * G].x, g[2 * G].y, g[2 * G].z, g[2 * G].w}, g1[4] = {g[2 * G + 1].x, g[2 * G + 1].y, g[2 * G + 1].z, g[2 * G + 1].w};
    const uint32_t x0[4] = {xr[2 * G].x, xr[2 * G].y, xr[2 * G].z, xr[2 * G].w}, x1[4] = {xr[2 * G + 1].x, xr[2 * G + 1].y, xr[2 * G + 1].z, xr[2 * G + 1].w};
#pragma unroll
    for (int i = 0; i < 4; i++) {
      const int a = KEEP + 4 * (4 * G + i);
      o0[i] = pack2(fmaf(y[a] + r[i].x, bf_lo(g0[i]), bf_lo(x0[i])), fmaf(y[a + 1] + r[i].y, bf_hi(g0[i]), bf_hi(x0[i])));
      o1[i] = pack2(fmaf(y[a + 2] + r[i].z, bf_lo(g1[i]), bf_lo(x1[i])), fmaf(y[a + 3] + r[i].w, bf_hi(g1[i]), bf_hi(x1[i])));
    }
    stg4(p.out + ooff + 32 * G, o0[0], o0[1], o0[2], o0[3]);
    stg4(p.out + ooff + 32 * G + 8 * DM, o1[0], o1[1], o1[2], o1[3]);
  }
  TLC(10);
}

__global__ void __cluster_dims__(2, 1, 1) __launch_bounds__(384, 1) fused_kernel(const __grid_constant__ Params p) {
  extern __shared__ __align__(1024) uint8_t smem_raw[];
  const uint32_t sm = (uint32_t)__cvta_generic_to_shared(smem_raw);
  const int tid = threadIdx.x, lane = tid & 31;
  const int warp = __shfl_sync(0xffffffffu, tid >> 5, 0);
  int lc;
  {
    const int c = blockIdx.x >> 1;
    if (c < 4) lc = 4 + c;
    else if (c < 36) lc = ((c - 4) & 7) * 8 + ((c - 4) >> 3);
    else lc = (1 + (c - 36) % 7) * 8 + 4 + (c - 36) / 7;
  }
  const int role = blockIdx.x & 1, cb = lc & 3, rb = lc >> 2, j = cb * 2 + role, lb = lc * 2 + role;
  const uint32_t bars = sm + OFF_BAR;
  TLC(0);
  if (warp == 8) {
    if (elect_one()) {
      for (int s = 0; s < NST; s++) { mbar_init(bars + BAR_FULL + 8 * s, 1); mbar_init(bars + BAR_EMPTY + 8 * s, 8); }
      mbar_init(bars + BAR_V1, 1); mbar_init(bars + BAR_V2, 2); mbar_init(bars + BAR_FREE, 1);
      mbar_init(bars + BAR_G, 1); mbar_init(bars + BAR_Y, 1); mbar_init(bars + BAR_OK, 8);
      asm volatile("fence.mbarrier_init.release.cluster;" ::: "memory");
      fence_async_smem();
      const CUtensorMap* md = j < 4 ? &p.mdre : &p.mdim;
      for (int k = 0; k < INIT_ST; k++) {
        mbar_expect_tx(bars + BAR_FULL + 8 * k, STB);
        tma2d(sm + k * STB, &p.mx, k * 64, rb * 128, bars + BAR_FULL + 8 * k);
        tma2d(sm + k * STB + 16384, md, k * 64, (j & 3) * 128, bars + BAR_FULL + 8 * k);
      }
      mbar_expect_tx(bars + BAR_G, 16384);
      mbar_expect_tx(bars + BAR_Y, 32768);
    }
    __syncwarp();
  }
  const unsigned epoch = (ld_rlx(&g_cnt[C_DONE]) >> 7) + 1;
  const uint32_t tag = epoch & 3;

  if (warp >= 8) {
    if (warp == 8) {
      __syncthreads();
      asm volatile("barrier.cluster.arrive.relaxed.aligned;" ::: "memory");
      asm volatile("setmaxnreg.dec.sync.aligned.u32 120;");
      if (elect_one()) {
        asm volatile("prefetch.tensormap [%0];" :: "l"(&p.mw1) : "memory");
        asm volatile("prefetch.tensormap [%0];" :: "l"(&p.mcr) : "memory");
        asm volatile("prefetch.tensormap [%0];" :: "l"(&p.mci) : "memory");
        asm volatile("prefetch.tensormap [%0];" :: "l"(&p.mab) : "memory");
        if (role) {
          asm volatile("prefetch.tensormap [%0];" :: "l"(&p.mh) : "memory");
          asm volatile("prefetch.tensormap [%0];" :: "l"(&p.mw2) : "memory");
        }
        int st = 0; uint32_t ph = 0;
        const int y0 = role ? 46 : 0;
        const int row0 = rb * 128;
#define P_ACQ() mbar_wait(bars + BAR_EMPTY + 8 * st, ph); const uint32_t fb = bars + BAR_FULL + 8 * st, sa = sm + st * STB, sb = sa + 16384; mbar_expect_tx(fb, STB)
#define P_ADV() if (++st == NST) { st = 0; ph ^= 1; }
        const CUtensorMap* md = j < 4 ? &p.mdre : &p.mdim;
        if (INIT_ST < NST) {
          mbar_wait(bars + BAR_FULL, 0);
          for (int k = INIT_ST; k < NST; k++) {
            mbar_expect_tx(bars + BAR_FULL + 8 * k, STB);
            tma2d(sm + k * STB, &p.mx, k * 64, row0, bars + BAR_FULL + 8 * k);
            tma2d(sm + k * STB + 16384, md, k * 64, (j & 3) * 128, bars + BAR_FULL + 8 * k);
          }
        }
        for (int k = NST; k < 8; k++) { P_ACQ(); tma2d(sa, &p.mx, k * 64, row0, fb); tma2d(sb, md, k * 64, (j & 3) * 128, fb); P_ADV(); }
        for (int k = 0; k < 16; k++) {
          P_ACQ(); tma2d(sa, &p.mx, (k & 7) * 64, row0, fb); tma3d(sb, &p.mw1, j * 224 + (k >> 3) * 96, (k & 7) * 64, 0, fb); P_ADV();
        }
        TLREC(11);
        if (!role) wait_cnt(&g_cnt[C_AB + cb * 32], 16 * epoch);
        wait_cnt(&g_cnt[C_AB + (4 + cb) * 32], 16 * epoch);
        asm volatile("fence.proxy.async.global;" ::: "memory");
        TLREC(12);
        const int nya = role ? 18 - NYB : 46;
        for (int k = y0; k < y0 + nya; k++) {
          P_ACQ(); tma2d(sa, k < 32 ? &p.mcr : &p.mci, (k & 31) * 64, row0, fb); tma3d(sb, &p.mab, 0, k * 64, cb * 2, fb); P_ADV();
        }
        if (role) {
          TLREC(13);
          wait_cnt(&g_cnt[C_H + rb * 32], 16 * epoch);
          asm volatile("fence.proxy.async.global;" ::: "memory");
          TLREC(14);
          for (int k = 0; k < 28; k++) {
            P_ACQ(); tma2d(sa, &p.mh, k * 64, row0, fb); tma5d(sb, &p.mw2, cb * 128, 2 * k, fb); tma5d(sb + 8192, &p.mw2, cb * 128 + 64, 2 * k, fb); P_ADV();
          }
          for (int k = 64 - NYB; k < 64; k++) {
            P_ACQ(); tma2d(sa, &p.mci, (k & 31) * 64, row0, fb); tma3d(sb, &p.mab, 0, k * 64, cb * 2, fb); P_ADV();
          }
        }
        red_add(&g_cnt[C_DONE]);
      }
    } else if (warp == 9) {
      const int d0 = lb * 8;
      const __nv_bfloat16* d = (d0 < DM ? p.dre + (size_t)d0 * DM : p.dim + (size_t)(d0 - DM) * DM) + lane * 8;
      uint4 u[8][2];
#pragma unroll
      for (int r = 0; r < 8; r++) { u[r][0] = ldg_nc(d + r * DM); u[r][1] = ldg_nc(d + r * DM + 256); }
      __syncthreads();
      asm volatile("barrier.cluster.arrive.relaxed.aligned;" ::: "memory");
      asm volatile("setmaxnreg.dec.sync.aligned.u32 120;");
      float t[8];
#pragma unroll
      for (int r = 0; r < 8; r++) t[r] = sum8(u[r][0]) + sum8(u[r][1]);
#pragma unroll
      for (int o = 4; o > 0; o >>= 1) {
#pragma unroll
        for (int r = 0; r < o; r++) {
          const bool up = lane & o;
          const float keep = up ? t[r + o] : t[r], give = up ? t[r] : t[r + o];
          t[r] = keep + __shfl_xor_sync(0xffffffffu, give, o);
        }
      }
      t[0] += __shfl_xor_sync(0xffffffffu, t[0], 8);
      t[0] += __shfl_xor_sync(0xffffffffu, t[0], 16);
      if (lane < 8) asm volatile("st.relaxed.gpu.global.u32 [%0], %1;" :: "l"(&g_cs[d0 + lane]), "r"(tagf(t[0], tag)) : "memory");
      if (lane == 0) TLREC(15);
      uint4 cv;
      { uint32_t n = 0; do { cv = ld_msg(&g_cs[j * 128 + lane * 4]); if (++n > (1u << 20)) __trap(); } while (__any_sync(0xffffffffu, stale(cv, tag))); }
      sts4(sm + OFF_VAB + lane * 16, cv.x, cv.y, cv.z, cv.w);
      __syncwarp();
      if (lane == 0) { mbar_arrive(bars + BAR_V1); TLREC(16); }
      if (lane == 0) { asm volatile("prefetch.tensormap [%0];" :: "l"(&p.sab) : "memory"); asm volatile("prefetch.tensormap [%0];" :: "l"(&p.sh) : "memory"); }
      for (int tile = 0; tile < 3; tile++) {
        bar_sync(1 + tile, 288);
        if (elect_one()) {
          TLREC(25 + tile);
          const CUtensorMap* m = tile ? &p.sh : &p.sab;
          const int c0 = tile == 0 ? (j & 3) * 128 : j * 224 + (tile - 1) * 96, r0 = (tile == 0 ? (j >> 2) * SEQ : 0) + rb * 128;
          for (int g = 0; g < (tile == 1 ? 3 : 4); g++) tma_st2d(m, sm + OFF_STG + g * 8192, c0 + g * 32, r0);
          asm volatile("cp.async.bulk.commit_group;\ncp.async.bulk.wait_group 0;" ::: "memory");
          red_add(tile ? &g_cnt[C_H + rb * 32] : &g_cnt[C_AB + j * 32]);
          mbar_arrive(bars + BAR_FREE);
          TLREC(17 + tile);
        }
        __syncwarp();
      }
    } else {
      const int cl = lane < 28 ? lane : 27;
      const __nv_bfloat16* w = p.w1 + (size_t)(rb * 32 + (warp - 10) * 16) * FF + j * 224 + cl * 8;
      uint4 v[16];
#pragma unroll
      for (int r = 0; r < 16; r++) v[r] = ldg_nc(w + (size_t)r * FF);
      __syncthreads();
      asm volatile("barrier.cluster.arrive.relaxed.aligned;" ::: "memory");
      asm volatile("setmaxnreg.dec.sync.aligned.u32 120;");
      float s[8] = {0.f, 0.f, 0.f, 0.f, 0.f, 0.f, 0.f, 0.f};
#pragma unroll
      for (int r = 0; r < 16; r++) {
        s[0] += bf_lo(v[r].x); s[1] += bf_hi(v[r].x); s[2] += bf_lo(v[r].y); s[3] += bf_hi(v[r].y);
        s[4] += bf_lo(v[r].z); s[5] += bf_hi(v[r].z); s[6] += bf_lo(v[r].w); s[7] += bf_hi(v[r].w);
      }
      float4* s4 = reinterpret_cast<float4*>(smem_raw);
      if (warp == 11) {
        if (lane < 28) { s4[OFF_VH / 16 + lane * 2] = make_float4(s[0], s[1], s[2], s[3]); s4[OFF_VH / 16 + lane * 2 + 1] = make_float4(s[4], s[5], s[6], s[7]); }
        const uint2 b2v = *reinterpret_cast<const uint2*>(p.b2 + cb * 128 + lane * 4);
        s4[OFF_B2 / 16 + lane] = make_float4(bf_lo(b2v.x), bf_hi(b2v.x), bf_lo(b2v.y), bf_hi(b2v.y));
      }
      bar_sync(4, 64);
      if (warp == 10 && lane < 28) {
        const float4 o0 = s4[OFF_VH / 16 + lane * 2], o1 = s4[OFF_VH / 16 + lane * 2 + 1];
        float* dst = &g_csw[rb * FF + j * 224 + lane * 8];
        st_msg(dst, tagf(s[0] + o0.x, tag), tagf(s[1] + o0.y, tag), tagf(s[2] + o0.z, tag), tagf(s[3] + o0.w, tag));
        st_msg(dst + 4, tagf(s[4] + o1.x, tag), tagf(s[5] + o1.y, tag), tagf(s[6] + o1.z, tag), tagf(s[7] + o1.w, tag));
      }
      bar_sync(4, 64);
      const int q = (warp - 10) * 28 + cl;
      const uint2 bb = *reinterpret_cast<const uint2*>(p.b1 + j * 224 + q * 4);
      float4 acc;
      uint32_t n = 0, bad;
      do {
        uint4 m[16];
#pragma unroll
        for (int r = 0; r < 16; r++) m[r] = ld_msg(&g_csw[r * FF + j * 224 + q * 4]);
        acc = make_float4(0.f, 0.f, 0.f, 0.f); bad = 0;
#pragma unroll
        for (int r = 0; r < 16; r++) {
          bad |= stale(m[r], tag);
          acc.x += __uint_as_float(m[r].x); acc.y += __uint_as_float(m[r].y); acc.z += __uint_as_float(m[r].z); acc.w += __uint_as_float(m[r].w);
        }
        if (++n > (1u << 20)) __trap();
      } while (__any_sync(0xffffffffu, bad));
      if (lane < 28) {
        s4[OFF_VH / 16 + q * 2] = make_float4(acc.x, acc.y, bf_lo(bb.x), bf_hi(bb.x));
        s4[OFF_VH / 16 + q * 2 + 1] = make_float4(acc.z, acc.w, bf_lo(bb.y), bf_hi(bb.y));
      }
      __syncwarp();
      if (lane == 0) { mbar_arrive(bars + BAR_V2); if (warp == 10) TLREC(24); }
    }
  } else {
    const int sr = rb * 128 + j * 16 + warp * 2;
    uint4 xv[2][2];
#pragma unroll
    for (int r = 0; r < 2; r++) { xv[r][0] = ldg_nc(p.x + (size_t)(sr + r) * DM + lane * 8); xv[r][1] = ldg_nc(p.x + (size_t)(sr + r) * DM + 256 + lane * 8); }
    __syncthreads();
    asm volatile("barrier.cluster.arrive.relaxed.aligned;" ::: "memory");
    asm volatile("setmaxnreg.inc.sync.aligned.u32 192;");
    Ctx c; c.sm = sm; c.lane = lane;
    c.da = (((sm + (warp >> 2) * 8192) & 0x3FFFF) >> 4) | (1u << 16); c.db = ((sm + 16384) & 0x3FFFF) >> 4;
    const int rl = warp * 16 + (lane >> 2);
    const int q8 = (lane & 3) * 8;
    const uint32_t stg = sm + OFF_STG + rl * 64 + (lane & 3) * 16;
    float P[64], Q[48], R[64], Y[64], M[64];
    mma_step<128, 0>(P, c, 0, 0, 0);
    TLC(1);
    mma_step<128, 0>(P, c, 1, 0, 1);
    {
      float mu[2], q[2];
#pragma unroll
      for (int r = 0; r < 2; r++) mu[r] = sum8(xv[r][0]) + sum8(xv[r][1]);
#pragma unroll
      for (int o = 16; o > 0; o >>= 1) { mu[0] += __shfl_xor_sync(0xffffffffu, mu[0], o); mu[1] += __shfl_xor_sync(0xffffffffu, mu[1], o); }
#pragma unroll
      for (int r = 0; r < 2; r++) {
        mu[r] *= 1.0f / DM;
        const uint32_t w[8] = {xv[r][0].x, xv[r][0].y, xv[r][0].z, xv[r][0].w, xv[r][1].x, xv[r][1].y, xv[r][1].z, xv[r][1].w};
        float qa = 0.f, qb = 0.f;
#pragma unroll
        for (int i = 0; i < 8; i++) { const float a = bf_lo(w[i]) - mu[r], b = bf_hi(w[i]) - mu[r]; qa = fmaf(a, a, qa); qb = fmaf(b, b, qb); }
        q[r] = qa + qb;
      }
#pragma unroll
      for (int o = 16; o > 0; o >>= 1) { q[0] += __shfl_xor_sync(0xffffffffu, q[0], o); q[1] += __shfl_xor_sync(0xffffffffu, q[1], o); }
      const float mean = (lane & 1) ? mu[1] : mu[0], var = ((lane & 1) ? q[1] : q[0]) * (1.0f / DM);
      const float m1 = bfr(mean), d1 = bfr(__fsqrt_rn(bfr(bfr(var) + 1e-5f))), i1 = __frcp_rn(d1);
      const float m2 = bfr((mean - m1) * i1), d2 = bfr(__fsqrt_rn(bfr(bfr(var * i1 * i1) + 1e-5f))), i2 = __frcp_rn(d2);
      if (lane < 2) st_msg(&g_stats[sr + lane], tagf(i1, tag), tagf(-m1 * i1, tag), tagf(i1 * i2, tag), tagf(-(m1 * i1 + m2) * i2, tag));
    }
    TLC(20);
    wg_wait<1>();
    release(c, 0);
    {
      int st = 2;
      for (int k = 2; k < 7; k++) {
        mma_step<128, 0>(P, c, st, k >= NST, 1);
        wg_wait<1>();
        release(c, st == 0 ? NST - 1 : st - 1);
        if (++st == NST) st = 0;
      }
    }
    mma_step<128, 0>(P, c, 7 % NST, 1, 1);
    uint4 m0 = ld_msg(&g_stats[rb * 128 + rl]), m1 = ld_msg(&g_stats[rb * 128 + rl + 8]);
    wg_wait<1>();
    release(c, 6 % NST);
    TLC(2);
    float4 s0, s1;
#pragma unroll
    for (int s = 8; s < 16; s++) {
      mma_step<96, 1>(Q, c, s % NST, (s / NST) & 1, s > 8);
      wg_wait<1>();
      release(c, (s - 1) % NST);
      if (s == 8) {
        reg_fence(P);
        uint32_t n = 0;
        while (stale(m0, tag) | stale(m1, tag)) { m0 = ld_msg(&g_stats[rb * 128 + rl]); m1 = ld_msg(&g_stats[rb * 128 + rl + 8]); if (++n > (1u << 20)) __trap(); }
        const float sg = j < 4 ? 1.f : -1.f;
        s0 = make_float4(__uint_as_float(m0.x) * sg, __uint_as_float(m0.y) * sg, __uint_as_float(m0.z), __uint_as_float(m0.w));
        s1 = make_float4(__uint_as_float(m1.x) * sg, __uint_as_float(m1.y) * sg, __uint_as_float(m1.z), __uint_as_float(m1.w));
        mbar_wait(bars + BAR_V1, 0);
        TLC(21);
        epi_ab<0>(P, c, s0.x, s0.y, s1.x, s1.y, stg);
        epi_ab<1>(P, c, s0.x, s0.y, s1.x, s1.y, stg);
      }
      if (s == 9) {
        epi_ab<2>(P, c, s0.x, s0.y, s1.x, s1.y, stg);
        epi_ab<3>(P, c, s0.x, s0.y, s1.x, s1.y, stg);
        fence_async_smem();
        bar_arrive(1, 288);
      }
    }
    TLC(3);
#pragma unroll
    for (int s = 16; s < 24; s++) {
      mma_step<128, 1>(R, c, s % NST, (s / NST) & 1, s > 16);
      wg_wait<1>();
      release(c, (s - 1) % NST);
      if (s == 16) { reg_fence(Q); mbar_wait(bars + BAR_V2, 0); mbar_wait(bars + BAR_FREE, 0); epi_h<0, 0>(Q, c, s0.z, s0.w, s1.z, s1.w, stg); }
      if (s == 18) epi_h<1, 1>(Q, c, s0.z, s0.w, s1.z, s1.w, stg);
      if (s == 20) { epi_h<2, 2>(Q, c, s0.z, s0.w, s1.z, s1.w, stg); fence_async_smem(); bar_arrive(2, 288); }
    }
    TLC(4);
#pragma unroll
    for (int s = 24; s < 30; s++) {
      mma_step<128, 1>(Y, c, s % NST, (s / NST) & 1, s > 24);
      wg_wait<1>();
      release(c, (s - 1) % NST);
      if (s == 24) { reg_fence(R); mbar_wait(bars + BAR_FREE, 1); epi_h<0, 3>(R, c, s0.z, s0.w, s1.z, s1.w, stg); }
      if (s == 25) epi_h<1, 4>(R, c, s0.z, s0.w, s1.z, s1.w, stg);
      if (s == 26) epi_h<2, 5>(R, c, s0.z, s0.w, s1.z, s1.w, stg);
      if (s == 27) { epi_h<3, 6>(R, c, s0.z, s0.w, s1.z, s1.w, stg); fence_async_smem(); bar_arrive(3, 288); }
    }
    TLC(5);
    int st = 30 % NST, pst = 29 % NST; uint32_t ph = (30 / NST) & 1;
    const int ny = role ? 12 - NYB : 40 - NYB;
    for (int k = 0; k < ny; k++) {
      mma_step<128, 1>(Y, c, st, ph, 1);
      wg_wait<1>();
      release(c, pst);
      pst = st; if (++st == NST) { st = 0; ph ^= 1; }
    }
    TLC(6);
    const size_t ooff = (size_t)(rb * 128 + rl) * DM + cb * 128 + role * 64 + q8;
    if (role) {
      for (int k = 0; k < 28; k++) {
        mma_step<128, 1>(M, c, st, ph, k);
        wg_wait<1>();
        release(c, pst);
        pst = st; if (++st == NST) { st = 0; ph ^= 1; }
      }
      TLC(7);
      tail<1>(Y, M, c, p, tid, ooff);
    } else {
      TLC(7);
      tail<0>(Y, M, c, p, tid, ooff);
    }
  }
}

typedef CUresult (*EncFn)(CUtensorMap*, CUtensorMapDataType, cuuint32_t, void*, const cuuint64_t*, const cuuint64_t*, const cuuint32_t*,
                          const cuuint32_t*, CUtensorMapInterleave, CUtensorMapSwizzle, CUtensorMapL2promotion, CUtensorMapFloatOOBfill);

void make_map(EncFn enc, CUtensorMap* m, const void* ptr, int nd, const uint64_t* dims, const uint64_t* strides, const uint32_t* box,
              CUtensorMapSwizzle sw = CU_TENSOR_MAP_SWIZZLE_128B) {
  const cuuint32_t es[5] = {1, 1, 1, 1, 1};
  cuuint64_t d[5], s[5]; cuuint32_t b[5];
  for (int i = 0; i < nd; i++) { d[i] = dims[i]; b[i] = box[i]; if (i + 1 < nd) s[i] = strides[i]; }
  enc(m, CU_TENSOR_MAP_DATA_TYPE_BFLOAT16, nd, const_cast<void*>(ptr), d, s, b, es, CU_TENSOR_MAP_INTERLEAVE_NONE,
      sw, CU_TENSOR_MAP_L2_PROMOTION_L2_128B, CU_TENSOR_MAP_FLOAT_OOB_FILL_NONE);
}

}

extern "C" void kernel_launch(void* const* d_in, const int* in_sizes, int n_in, void* d_out, int out_size) {
  static Params prm;
  static const void* key[11];
  static EncFn enc = nullptr;
  bool same = enc != nullptr && key[10] == d_out;
  for (int i = 0; i < 10 && same; i++) same = key[i] == d_in[i];
  if (!same) {
    if (!enc) {
      cudaDriverEntryPointQueryResult q;
      cudaGetDriverEntryPoint("cuTensorMapEncodeTiled", reinterpret_cast<void**>(&enc), cudaEnableDefault, &q);
      cudaFuncSetAttribute(fused_kernel, cudaFuncAttributeMaxDynamicSharedMemorySize, SMEM_BYTES);
    }
    void *ab, *h;
    cudaGetSymbolAddress(&ab, g_ab);
    cudaGetSymbolAddress(&h, g_h);
    const uint32_t box2[2] = {64, 128}, box3[3] = {64, 64, 2}, box5[5] = {64, 2, 4, 4, 2};
    { const uint64_t d[2] = {DM, SEQ}, s[1] = {DM * 2}; make_map(enc, &prm.mx, d_in[0], 2, d, s, box2); }
    { const uint64_t d[2] = {SEQ, SEQ}, s[1] = {SEQ * 2}; make_map(enc, &prm.mcr, d_in[1], 2, d, s, box2); make_map(enc, &prm.mci, d_in[2], 2, d, s, box2); }
    { const uint64_t d[2] = {DM, DM}, s[1] = {DM * 2}; make_map(enc, &prm.mdre, d_in[3], 2, d, s, box2); make_map(enc, &prm.mdim, d_in[4], 2, d, s, box2); }
    { const uint64_t d[3] = {FF, DM, 2}, s[2] = {FF * 2, 128}; make_map(enc, &prm.mw1, d_in[6], 3, d, s, box3); }
    { const uint64_t d[3] = {64, 2 * SEQ, 8}, s[2] = {DM * 2, 128}; make_map(enc, &prm.mab, ab, 3, d, s, box3); }
    { const uint64_t d[2] = {FF, SEQ}, s[1] = {FF * 2}; make_map(enc, &prm.mh, h, 2, d, s, box2); }
    { const uint64_t d[5] = {DM, 2, 4, 4, FF / 32}, s[4] = {DM * 2, 8 * DM * 2, 2 * DM * 2, 32 * DM * 2}; make_map(enc, &prm.mw2, d_in[8], 5, d, s, box5); }
    const uint32_t boxs[2] = {32, 128};
    { const uint64_t d[2] = {DM, 2 * SEQ}, s[1] = {DM * 2}; make_map(enc, &prm.sab, ab, 2, d, s, boxs, CU_TENSOR_MAP_SWIZZLE_NONE); }
    { const uint64_t d[2] = {FF, SEQ}, s[1] = {FF * 2}; make_map(enc, &prm.sh, h, 2, d, s, boxs, CU_TENSOR_MAP_SWIZZLE_NONE); }
    prm.x = (const __nv_bfloat16*)d_in[0]; prm.dre = (const __nv_bfloat16*)d_in[3]; prm.dim = (const __nv_bfloat16*)d_in[4];
    prm.w1 = (const __nv_bfloat16*)d_in[6]; prm.b1 = (const __nv_bfloat16*)d_in[7]; prm.w2 = (const __nv_bfloat16*)d_in[8];
    prm.b2 = (const __nv_bfloat16*)d_in[9]; prm.out = (__nv_bfloat16*)d_out;
    for (int i = 0; i < 10; i++) key[i] = d_in[i];
    key[10] = d_out;
  }
  fused_kernel<<<128, 384, SMEM_BYTES>>>(prm);
}
```

```cpp
#include <cuda_runtime.h>
#include <cuda_bf16.h>
#include <cuda.h>
#include <stdint.h>

namespace {

constexpr int SEQ = 2048, DM = 512, FF = 1792;
constexpr int NST = 6;
constexpr int STB = 32768;
constexpr int OFF_STG = NST * STB;
constexpr int OFF_G = OFF_STG;
constexpr int OFF_VAB = OFF_STG + 32768;
constexpr int OFF_VH = OFF_VAB + 512;
constexpr int OFF_B2 = OFF_VH + 1792;
constexpr int OFF_BAR = OFF_B2 + 256;
constexpr int SMEM_BYTES = OFF_BAR + 288;
static_assert(SMEM_BYTES <= 232448, "smem");
constexpr int BAR_FULL = 0, BAR_EMPTY = 48, BAR_V1 = 96, BAR_G = 104, BAR_Y = 112, BAR_OK = 120, BAR_V2 = 128, BAR_FREE = 136,
              BAR_E = 144, OFF_EPOCH = 152, BAR_XF = 160, BAR_BF = 224, BAR_BE = 256;
__host__ __device__ constexpr int xslot(int k) { return (k < 4 ? k : 2 * k - 4) * 16384; }
__host__ __device__ constexpr int bslot(int i) { return (5 + 2 * i) * 16384; }
#define DLY_D 0
#define DLY_W 3
constexpr int NSTEPS = 70;
constexpr int NYB = 6;
constexpr int LAND_STAGE = (NSTEPS - 6) % NST;

constexpr int C_DONE = 0, C_AB = 64, C_H = 64 + 8 * 32;

struct Params {
  CUtensorMap mx, mdre, mdim, mw1, mcr, mci, mab, mh, mw2, sab, sh;
  const __nv_bfloat16 *x, *dre, *dim, *w1, *b1, *w2, *b2;
  __nv_bfloat16* out;
};

__device__ __align__(1024) __nv_bfloat16 g_ab[2 * SEQ * DM];
__device__ __align__(1024) __nv_bfloat16 g_h[SEQ * FF];
__device__ float4 g_stats[SEQ];
__device__ __align__(16) float g_cs[2 * DM];
__device__ __align__(16) float g_csw[16 * FF];
__device__ unsigned g_cnt[64 + 8 * 32 + 16 * 32];
#define TLREC(ev) do {} while (0)
#define TLC(ev) do {} while (0)

__device__ __forceinline__ void mbar_init(uint32_t bar, uint32_t cnt) { asm volatile("mbarrier.init.shared::cta.b64 [%0], %1;" :: "r"(bar), "r"(cnt) : "memory"); }
__device__ __forceinline__ void mbar_expect_tx(uint32_t bar, uint32_t bytes) { asm volatile("mbarrier.arrive.expect_tx.shared::cta.b64 _, [%0], %1;" :: "r"(bar), "r"(bytes) : "memory"); }
__device__ __forceinline__ void mbar_arrive(uint32_t bar) { asm volatile("mbarrier.arrive.shared::cta.b64 _, [%0];" :: "r"(bar) : "memory"); }
__device__ __forceinline__ void mbar_arrive_cluster(uint32_t remote_bar) { asm volatile("mbarrier.arrive.shared::cluster.b64 _, [%0];" :: "r"(remote_bar) : "memory"); }
__device__ __forceinline__ uint32_t mapa(uint32_t addr, uint32_t cta) { uint32_t r; asm("mapa.shared::cluster.u32 %0, %1, %2;" : "=r"(r) : "r"(addr), "r"(cta)); return r; }
__device__ __forceinline__ bool mbar_try(uint32_t bar, uint32_t parity) {
  uint32_t ok;
  asm volatile("{\n.reg .pred p;\nmbarrier.try_wait.parity.shared::cta.b64 p, [%1], %2;\nselp.u32 %0, 1, 0, p;\n}" : "=r"(ok) : "r"(bar), "r"(parity) : "memory");
  return ok;
}
__device__ __forceinline__ void mbar_wait(uint32_t bar, uint32_t parity) {
  if (mbar_try(bar, parity)) return;
  uint32_t n = 0;
  while (!mbar_try(bar, parity)) { if (++n > (1u << 20)) __trap(); }
}
__device__ __forceinline__ bool elect_one() {
  uint32_t p;
  asm volatile("{\n.reg .pred p;\nelect.sync _|p, 0xffffffff;\nselp.u32 %0, 1, 0, p;\n}" : "=r"(p));
  return p;
}
__device__ __forceinline__ void tma2d(uint32_t dst, const CUtensorMap* m, int c0, int c1, uint32_t bar) {
  asm volatile("cp.async.bulk.tensor.2d.shared::cluster.global.mbarrier::complete_tx::bytes [%0], [%1, {%3, %4}], [%2];"
    :: "r"(dst), "l"(m), "r"(bar), "r"(c0), "r"(c1) : "memory");
}
__device__ __forceinline__ void tma3d(uint32_t dst, const CUtensorMap* m, int c0, int c1, int c2, uint32_t bar) {
  asm volatile("cp.async.bulk.tensor.3d.shared::cluster.global.mbarrier::complete_tx::bytes [%0], [%1, {%3, %4, %5}], [%2];"
    :: "r"(dst), "l"(m), "r"(bar), "r"(c0), "r"(c1), "r"(c2) : "memory");
}
__device__ __forceinline__ void tma5d(uint32_t dst, const CUtensorMap* m, int c0, int c4, uint32_t bar) {
  asm volatile("cp.async.bulk.tensor.5d.shared::cluster.global.mbarrier::complete_tx::bytes [%0], [%1, {%3, %5, %5, %5, %4}], [%2];"
    :: "r"(dst), "l"(m), "r"(bar), "r"(c0), "r"(c4), "r"(0) : "memory");
}
__device__ __forceinline__ void tma_pf2d(const CUtensorMap* m, int c0, int c1) {
  asm volatile("cp.async.bulk.prefetch.tensor.2d.L2.global [%0, {%1, %2}];" :: "l"(m), "r"(c0), "r"(c1) : "memory");
}
__device__ __forceinline__ void wg_fence() { asm volatile("wgmma.fence.sync.aligned;" ::: "memory"); }
__device__ __forceinline__ void wg_commit() { asm volatile("wgmma.commit_group.sync.aligned;" ::: "memory"); }
template <int N> __device__ __forceinline__ void wg_wait() { asm volatile("wgmma.wait_group.sync.aligned %0;" :: "n"(N) : "memory"); }
template <int N> __device__ __forceinline__ void reg_fence(float (&d)[N]) {
#pragma unroll
  for (int i = 0; i < N; i++) asm volatile("" : "+f"(d[i]) :: "memory");
}
__device__ __forceinline__ void wgmma4_n128_tb0(float (&d)[64], uint32_t a, uint32_t b, int scale_d) {
  asm volatile("{\n.reg .pred p;\n.reg .b32 la, lb, hi;\n.reg .b64 da, db;\nsetp.ne.b32 p, %66, 0;\nmov.b32 hi, 0x40000040;\n"
    "add.u32 la, %64, 0;\nadd.u32 lb, %65, 0;\nmov.b64 da, {la, hi};\nmov.b64 db, {lb, hi};\n"
    "wgmma.mma_async.sync.aligned.m64n128k16.f32.bf16.bf16 "
    "{%0, %1, %2, %3, %4, %5, %6, %7, %8, %9, %10, %11, %12, %13, %14, %15, %16, %17, %18, %19, %20, %21, %22, %23, %24, %25, %26, %27, %28, %29, %30, %31, %32, %33, %34, %35, %36, %37, %38, %39, %40, %41, %42, %43, %44, %45, %46, %47, %48, %49, %50, %51, %52, %53, %54, %55, %56, %57, %58, %59, %60, %61, %62, %63}, "
    "da, db, p, 1, 1, 0, 0;\n"
    "add.u32 la, %64, 2;\nadd.u32 lb, %65, 2;\nmov.b64 da, {la, hi};\nmov.b64 db, {lb, hi};\n"
    "wgmma.mma_async.sync.aligned.m64n128k16.f32.bf16.bf16 "
    "{%0, %1, %2, %3, %4, %5, %6, %7, %8, %9, %10, %11, %12, %13, %14, %15, %16, %17, %18, %19, %20, %21, %22, %23, %24, %25, %26, %27, %28, %29, %30, %31, %32, %33, %34, %35, %36, %37, %38, %39, %40, %41, %42, %43, %44, %45, %46, %47, %48, %49, %50, %51, %52, %53, %54, %55, %56, %57, %58, %59, %60, %61, %62, %63}, "
    "da, db, 1, 1, 1, 0, 0;\n"
    "add.u32 la, %64, 4;\nadd.u32 lb, %65, 4;\nmov.b64 da, {la, hi};\nmov.b64 db, {lb, hi};\n"
    "wgmma.mma_async.sync.aligned.m64n128k16.f32.bf16.bf16 "
    "{%0, %1, %2, %3, %4, %5, %6, %7, %8, %9, %10, %11, %12, %13, %14, %15, %16, %17, %18, %19, %20, %21, %22, %23, %24, %25, %26, %27, %28, %29, %30, %31, %32, %33, %34, %35, %36, %37, %38, %39, %40, %41, %42, %43, %44, %45, %46, %47, %48, %49, %50, %51, %52, %53, %54, %55, %56, %57, %58, %59, %60, %61, %62, %63}, "
    "da, db, 1, 1, 1, 0, 0;\n"
    "add.u32 la, %64, 6;\nadd.u32 lb, %65, 6;\nmov.b64 da, {la, hi};\nmov.b64 db, {lb, hi};\n"
    "wgmma.mma_async.sync.aligned.m64n128k16.f32.bf16.bf16 "
    "{%0, %1, %2, %3, %4, %5, %6, %7, %8, %9, %10, %11, %12, %13, %14, %15, %16, %17, %18, %19, %20, %21, %22, %23, %24, %25, %26, %27, %28, %29, %30, %31, %32, %33, %34, %35, %36, %37, %38, %39, %40, %41, %42, %43, %44, %45, %46, %47, %48, %49, %50, %51, %52, %53, %54, %55, %56, %57, %58, %59, %60, %61, %62, %63}, "
    "da, db, 1, 1, 1, 0, 0;\n"
    "}\n"
    : "+f"(d[0]), "+f"(d[1]), "+f"(d[2]), "+f"(d[3]), "+f"(d[4]), "+f"(d[5]), "+f"(d[6]), "+f"(d[7]), "+f"(d[8]), "+f"(d[9]), "+f"(d[10]), "+f"(d[11]), "+f"(d[12]), "+f"(d[13]), "+f"(d[14]), "+f"(d[15]), "+f"(d[16]), "+f"(d[17]), "+f"(d[18]), "+f"(d[19]), "+f"(d[20]), "+f"(d[21]), "+f"(d[22]), "+f"(d[23]), "+f"(d[24]), "+f"(d[25]), "+f"(d[26]), "+f"(d[27]), "+f"(d[28]), "+f"(d[29]), "+f"(d[30]), "+f"(d[31]), "+f"(d[32]), "+f"(d[33]), "+f"(d[34]), "+f"(d[35]), "+f"(d[36]), "+f"(d[37]), "+f"(d[38]), "+f"(d[39]), "+f"(d[40]), "+f"(d[41]), "+f"(d[42]), "+f"(d[43]), "+f"(d[44]), "+f"(d[45]), "+f"(d[46]), "+f"(d[47]), "+f"(d[48]), "+f"(d[49]), "+f"(d[50]), "+f"(d[51]), "+f"(d[52]), "+f"(d[53]), "+f"(d[54]), "+f"(d[55]), "+f"(d[56]), "+f"(d[57]), "+f"(d[58]), "+f"(d[59]), "+f"(d[60]), "+f"(d[61]), "+f"(d[62]), "+f"(d[63])
    : "r"(a), "r"(b), "r"(scale_d));
}
__device__ __forceinline__ void wgmma4_n128_tb1(float (&d)[64], uint32_t a, uint32_t b, int scale_d) {
  asm volatile("{\n.reg .pred p;\n.reg .b32 la, lb, hi;\n.reg .b64 da, db;\nsetp.ne.b32 p, %66, 0;\nmov.b32 hi, 0x40000040;\n"
    "add.u32 la, %64, 0;\nadd.u32 lb, %65, 0;\nmov.b64 da, {la, hi};\nmov.b64 db, {lb, hi};\n"
    "wgmma.mma_async.sync.aligned.m64n128k16.f32.bf16.bf16 "
    "{%0, %1, %2, %3, %4, %5, %6, %7, %8, %9, %10, %11, %12, %13, %14, %15, %16, %17, %18, %19, %20, %21, %22, %23, %24, %25, %26, %27, %28, %29, %30, %31, %32, %33, %34, %35, %36, %37, %38, %39, %40, %41, %42, %43, %44, %45, %46, %47, %48, %49, %50, %51, %52, %53, %54, %55, %56, %57, %58, %59, %60, %61, %62, %63}, "
    "da, db, p, 1, 1, 0, 1;\n"
    "add.u32 la, %64, 2;\nadd.u32 lb, %65, 128;\nmov.b64 da, {la, hi};\nmov.b64 db, {lb, hi};\n"
    "wgmma.mma_async.sync.aligned.m64n128k16.f32.bf16.bf16 "
    "{%0, %1, %2, %3, %4, %5, %6, %7, %8, %9, %10, %11, %12, %13, %14, %15, %16, %17, %18, %19, %20, %21, %22, %23, %24, %25, %26, %27, %28, %29, %30, %31, %32, %33, %34, %35, %36, %37, %38, %39, %40, %41, %42, %43, %44, %45, %46, %47, %48, %49, %50, %51, %52, %53, %54, %55, %56, %57, %58, %59, %60, %61, %62, %63}, "
    "da, db, 1, 1, 1, 0, 1;\n"
    "add.u32 la, %64, 4;\nadd.u32 lb, %65, 256;\nmov.b64 da, {la, hi};\nmov.b64 db, {lb, hi};\n"
    "wgmma.mma_async.sync.aligned.m64n128k16.f32.bf16.bf16 "
    "{%0, %1, %2, %3, %4, %5, %6, %7, %8, %9, %10, %11, %12, %13, %14, %15, %16, %17, %18, %19, %20, %21, %22, %23, %24, %25, %26, %27, %28, %29, %30, %31, %32, %33, %34, %35, %36, %37, %38, %39, %40, %41, %42, %43, %44, %45, %46, %47, %48, %49, %50, %51, %52, %53, %54, %55, %56, %57, %58, %59, %60, %61, %62, %63}, "
    "da, db, 1, 1, 1, 0, 1;\n"
    "add.u32 la, %64, 6;\nadd.u32 lb, %65, 384;\nmov.b64 da, {la, hi};\nmov.b64 db, {lb, hi};\n"
    "wgmma.mma_async.sync.aligned.m64n128k16.f32.bf16.bf16 "
    "{%0, %1, %2, %3, %4, %5, %6, %7, %8, %9, %10, %11, %12, %13, %14, %15, %16, %17, %18, %19, %20, %21, %22, %23, %24, %25, %26, %27, %28, %29, %30, %31, %32, %33, %34, %35, %36, %37, %38, %39, %40, %41, %42, %43, %44, %45, %46, %47, %48, %49, %50, %51, %52, %53, %54, %55, %56, %57, %58, %59, %60, %61, %62, %63}, "
    "da, db, 1, 1, 1, 0, 1;\n"
    "}\n"
    : "+f"(d[0]), "+f"(d[1]), "+f"(d[2]), "+f"(d[3]), "+f"(d[4]), "+f"(d[5]), "+f"(d[6]), "+f"(d[7]), "+f"(d[8]), "+f"(d[9]), "+f"(d[10]), "+f"(d[11]), "+f"(d[12]), "+f"(d[13]), "+f"(d[14]), "+f"(d[15]), "+f"(d[16]), "+f"(d[17]), "+f"(d[18]), "+f"(d[19]), "+f"(d[20]), "+f"(d[21]), "+f"(d[22]), "+f"(d[23]), "+f"(d[24]), "+f"(d[25]), "+f"(d[26]), "+f"(d[27]), "+f"(d[28]), "+f"(d[29]), "+f"(d[30]), "+f"(d[31]), "+f"(d[32]), "+f"(d[33]), "+f"(d[34]), "+f"(d[35]), "+f"(d[36]), "+f"(d[37]), "+f"(d[38]), "+f"(d[39]), "+f"(d[40]), "+f"(d[41]), "+f"(d[42]), "+f"(d[43]), "+f"(d[44]), "+f"(d[45]), "+f"(d[46]), "+f"(d[47]), "+f"(d[48]), "+f"(d[49]), "+f"(d[50]), "+f"(d[51]), "+f"(d[52]), "+f"(d[53]), "+f"(d[54]), "+f"(d[55]), "+f"(d[56]), "+f"(d[57]), "+f"(d[58]), "+f"(d[59]), "+f"(d[60]), "+f"(d[61]), "+f"(d[62]), "+f"(d[63])
    : "r"(a), "r"(b), "r"(scale_d));
}
__device__ __forceinline__ void wgmma4_n96_tb1(float (&d)[48], uint32_t a, uint32_t b, int scale_d) {
  asm volatile("{\n.reg .pred p;\n.reg .b32 la, lb, hi;\n.reg .b64 da, db;\nsetp.ne.b32 p, %50, 0;\nmov.b32 hi, 0x40000040;\n"
    "add.u32 la, %48, 0;\nadd.u32 lb, %49, 0;\nmov.b64 da, {la, hi};\nmov.b64 db, {lb, hi};\n"
    "wgmma.mma_async.sync.aligned.m64n96k16.f32.bf16.bf16 "
    "{%0, %1, %2, %3, %4, %5, %6, %7, %8, %9, %10, %11, %12, %13, %14, %15, %16, %17, %18, %19, %20, %21, %22, %23, %24, %25, %26, %27, %28, %29, %30, %31, %32, %33, %34, %35, %36, %37, %38, %39, %40, %41, %42, %43, %44, %45, %46, %47}, "
    "da, db, p, 1, 1, 0, 1;\n"
    "add.u32 la, %48, 2;\nadd.u32 lb, %49, 128;\nmov.b64 da, {la, hi};\nmov.b64 db, {lb, hi};\n"
    "wgmma.mma_async.sync.aligned.m64n96k16.f32.bf16.bf16 "
    "{%0, %1, %2, %3, %4, %5, %6, %7, %8, %9, %10, %11, %12, %13, %14, %15, %16, %17, %18, %19, %20, %21, %22, %23, %24, %25, %26, %27, %28, %29, %30, %31, %32, %33, %34, %35, %36, %37, %38, %39, %40, %41, %42, %43, %44, %45, %46, %47}, "
    "da, db, 1, 1, 1, 0, 1;\n"
    "add.u32 la, %48, 4;\nadd.u32 lb, %49, 256;\nmov.b64 da, {la, hi};\nmov.b64 db, {lb, hi};\n"
    "wgmma.mma_async.sync.aligned.m64n96k16.f32.bf16.bf16 "
    "{%0, %1, %2, %3, %4, %5, %6, %7, %8, %9, %10, %11, %12, %13, %14, %15, %16, %17, %18, %19, %20, %21, %22, %23, %24, %25, %26, %27, %28, %29, %30, %31, %32, %33, %34, %35, %36, %37, %38, %39, %40, %41, %42, %43, %44, %45, %46, %47}, "
    "da, db, 1, 1, 1, 0, 1;\n"
    "add.u32 la, %48, 6;\nadd.u32 lb, %49, 384;\nmov.b64 da, {la, hi};\nmov.b64 db, {lb, hi};\n"
    "wgmma.mma_async.sync.aligned.m64n96k16.f32.bf16.bf16 "
    "{%0, %1, %2, %3, %4, %5, %6, %7, %8, %9, %10, %11, %12, %13, %14, %15, %16, %17, %18, %19, %20, %21, %22, %23, %24, %25, %26, %27, %28, %29, %30, %31, %32, %33, %34, %35, %36, %37, %38, %39, %40, %41, %42, %43, %44, %45, %46, %47}, "
    "da, db, 1, 1, 1, 0, 1;\n"
    "}\n"
    : "+f"(d[0]), "+f"(d[1]), "+f"(d[2]), "+f"(d[3]), "+f"(d[4]), "+f"(d[5]), "+f"(d[6]), "+f"(d[7]), "+f"(d[8]), "+f"(d[9]), "+f"(d[10]), "+f"(d[11]), "+f"(d[12]), "+f"(d[13]), "+f"(d[14]), "+f"(d[15]), "+f"(d[16]), "+f"(d[17]), "+f"(d[18]), "+f"(d[19]), "+f"(d[20]), "+f"(d[21]), "+f"(d[22]), "+f"(d[23]), "+f"(d[24]), "+f"(d[25]), "+f"(d[26]), "+f"(d[27]), "+f"(d[28]), "+f"(d[29]), "+f"(d[30]), "+f"(d[31]), "+f"(d[32]), "+f"(d[33]), "+f"(d[34]), "+f"(d[35]), "+f"(d[36]), "+f"(d[37]), "+f"(d[38]), "+f"(d[39]), "+f"(d[40]), "+f"(d[41]), "+f"(d[42]), "+f"(d[43]), "+f"(d[44]), "+f"(d[45]), "+f"(d[46]), "+f"(d[47])
    : "r"(a), "r"(b), "r"(scale_d));
}

__device__ __forceinline__ void bar_arrive(int id, int n) { asm volatile("bar.arrive %0, %1;" :: "r"(id), "r"(n) : "memory"); }
__device__ __forceinline__ void bar_sync(int id, int n) { asm volatile("bar.sync %0, %1;" :: "r"(id), "r"(n) : "memory"); }
__device__ __forceinline__ unsigned ld_rlx(const unsigned* p) { unsigned v; asm volatile("ld.relaxed.gpu.global.u32 %0, [%1];" : "=r"(v) : "l"(p) : "memory"); return v; }
__device__ __forceinline__ void red_add(unsigned* p) { asm volatile("red.relaxed.gpu.global.add.u32 [%0], 1;" :: "l"(p) : "memory"); }
__device__ __forceinline__ void wait_cnt(const unsigned* p, unsigned target) {
  uint32_t n = 0;
  while ((int)(ld_rlx(p) - target) < 0) { if (++n > (1u << 20)) __trap(); }
}
__device__ __forceinline__ float bf_lo(uint32_t v) { return __uint_as_float(v << 16); }
__device__ __forceinline__ float bf_hi(uint32_t v) { return __uint_as_float(v & 0xffff0000u); }
__device__ __forceinline__ uint32_t pack2(float lo, float hi) { uint32_t r; asm("cvt.rn.bf16x2.f32 %0, %1, %2;" : "=r"(r) : "f"(hi), "f"(lo)); return r; }
__device__ __forceinline__ float bfr(float v) { return __bfloat162float(__float2bfloat16_rn(v)); }
__device__ __forceinline__ float gelu_f(float t) {
  const float k0 = 0.7978845608028654f, k1 = k0 * 0.044715f;
  float th; asm("tanh.approx.f32 %0, %1;" : "=f"(th) : "f"(t * fmaf(t * t, k1, k0)));
  const float hf = 0.5f * t;
  return fmaf(hf, th, hf);
}
__device__ __forceinline__ float silu_f(float z) {
  const float hz = 0.5f * z;
  float th; asm("tanh.approx.f32 %0, %1;" : "=f"(th) : "f"(hz));
  return fmaf(hz, th, hz);
}
__device__ __forceinline__ uint32_t tagf(float v, uint32_t tag) { return (__float_as_uint(v) & ~3u) | tag; }
__device__ __forceinline__ uint4 ld_msg(const void* p) { uint4 v; asm volatile("ld.relaxed.gpu.global.v4.u32 {%0,%1,%2,%3}, [%4];" : "=r"(v.x), "=r"(v.y), "=r"(v.z), "=r"(v.w) : "l"(p) : "memory"); return v; }
__device__ __forceinline__ void st_msg(void* p, uint32_t a, uint32_t b, uint32_t c, uint32_t d) { asm volatile("st.relaxed.gpu.global.v4.u32 [%0], {%1,%2,%3,%4};" :: "l"(p), "r"(a), "r"(b), "r"(c), "r"(d) : "memory"); }
__device__ __forceinline__ uint32_t stale(const uint4& v, uint32_t tag) { return ((v.x ^ tag) | (v.y ^ tag) | (v.z ^ tag) | (v.w ^ tag)) & 3u; }
__device__ __forceinline__ void sts4(uint32_t a, uint32_t x, uint32_t y, uint32_t z, uint32_t w) { asm volatile("st.shared.v4.u32 [%0], {%1,%2,%3,%4};" :: "r"(a), "r"(x), "r"(y), "r"(z), "r"(w) : "memory"); }
__device__ __forceinline__ void tma_st2d(const CUtensorMap* m, uint32_t src, int c0, int c1) {
  asm volatile("cp.async.bulk.tensor.2d.global.shared::cta.bulk_group [%0, {%2, %3}], [%1];" :: "l"(m), "r"(src), "r"(c0), "r"(c1) : "memory");
}
__device__ __forceinline__ void fence_async_smem() { asm volatile("fence.proxy.async.shared::cta;" ::: "memory"); }
__device__ __forceinline__ uint4 ldg_nc(const void* p) { uint4 v; asm volatile("ld.global.nc.v4.u32 {%0,%1,%2,%3}, [%4];" : "=r"(v.x), "=r"(v.y), "=r"(v.z), "=r"(v.w) : "l"(p)); return v; }
__device__ __forceinline__ void stg4(void* p, uint32_t a, uint32_t b, uint32_t c, uint32_t d) { asm volatile("st.global.v4.u32 [%0], {%1,%2,%3,%4};" :: "l"(p), "r"(a), "r"(b), "r"(c), "r"(d) : "memory"); }
__device__ __forceinline__ float4 lds4f(uint32_t a) { float4 v; asm volatile("ld.shared.v4.f32 {%0,%1,%2,%3}, [%4];" : "=f"(v.x), "=f"(v.y), "=f"(v.z), "=f"(v.w) : "r"(a)); return v; }
__device__ __forceinline__ uint4 lds4u(uint32_t a) { uint4 v; asm volatile("ld.shared.v4.u32 {%0,%1,%2,%3}, [%4];" : "=r"(v.x), "=r"(v.y), "=r"(v.z), "=r"(v.w) : "r"(a) : "memory"); return v; }
__device__ __forceinline__ float2 lds2f(uint32_t a) { float2 v; asm volatile("ld.shared.v2.f32 {%0,%1}, [%2];" : "=f"(v.x), "=f"(v.y) : "r"(a)); return v; }
__device__ __forceinline__ void st_async4(uint32_t raddr, uint32_t a, uint32_t b, uint32_t c, uint32_t d, uint32_t rbar) {
  asm volatile("st.async.weak.shared::cluster.mbarrier::complete_tx::bytes.v4.b32 [%0], {%1,%2,%3,%4}, [%5];"
    :: "r"(raddr), "r"(a), "r"(b), "r"(c), "r"(d), "r"(rbar) : "memory");
}
__device__ __forceinline__ float wsum(float v) {
#pragma unroll
  for (int o = 16; o > 0; o >>= 1) v += __shfl_xor_sync(0xffffffffu, v, o);
  return v;
}
__device__ __forceinline__ float sum8(const uint4& v) {
  return ((bf_lo(v.x) + bf_hi(v.x)) + (bf_lo(v.y) + bf_hi(v.y))) + ((bf_lo(v.z) + bf_hi(v.z)) + (bf_lo(v.w) + bf_hi(v.w)));
}

struct Ctx {
  uint32_t sm;
  uint32_t da;
  uint32_t db;
  int lane;
};

template <int N, int TB>
__device__ __forceinline__ void mma_step(float (&acc)[N / 2], const Ctx& c, int st, uint32_t ph, int accum) {
  mbar_wait(c.sm + OFF_BAR + BAR_FULL + 8 * st, ph);
  const uint32_t a = c.da + st * (STB >> 4), b = c.db + st * (STB >> 4) + (TB ? (512u << 16) : (1u << 16));
  wg_fence();
  if constexpr (N == 128 && TB == 0) wgmma4_n128_tb0(acc, a, b, accum);
  if constexpr (N == 128 && TB == 1) wgmma4_n128_tb1(acc, a, b, accum);
  if constexpr (N == 96) wgmma4_n96_tb1(acc, a, b, accum);
  wg_commit();
}
template <int N, int TB, int S>
__device__ __forceinline__ void mma_step1(float (&acc)[N / 2], const Ctx& c) {
  if (S < 8) mbar_wait(c.sm + OFF_BAR + BAR_XF + 8 * S, 0);
  mbar_wait(c.sm + OFF_BAR + BAR_BF + 8 * (S & 3), (S >> 2) & 1);
  const uint32_t a = c.da + (xslot(S & 7) >> 4), b = c.db + ((bslot(S & 3) - 16384) >> 4) + (TB ? (512u << 16) : (1u << 16));
  wg_fence();
  if constexpr (N == 128 && TB == 0) wgmma4_n128_tb0(acc, a, b, (S & 7) != 0);
  if constexpr (N == 128 && TB == 1) wgmma4_n128_tb1(acc, a, b, (S & 7) != 0);
  if constexpr (N == 96) wgmma4_n96_tb1(acc, a, b, (S & 7) != 0);
  wg_commit();
}
template <int S>
__device__ __forceinline__ void release1(const Ctx& c) {
  if (c.lane == 0) {
    if (S < 20) mbar_arrive(c.sm + OFF_BAR + BAR_BE + 8 * (S & 3));
    if (S == 17) mbar_arrive(c.sm + OFF_BAR + BAR_EMPTY);
    if constexpr (S >= 19) mbar_arrive(c.sm + OFF_BAR + BAR_EMPTY + 8 * (S - 18));
  }
}
template <int V> struct IC { static constexpr int value = V; };
template <int S0, int S1, class F>
__device__ __forceinline__ void static_for(F&& f) {
  if constexpr (S0 < S1) { f(IC<S0>{}); static_for<S0 + 1, S1>(f); }
}
__device__ __forceinline__ void release(const Ctx& c, int st) {
  if (c.lane == 0) mbar_arrive(c.sm + OFF_BAR + BAR_EMPTY + 8 * st);
}

template <int G>
__device__ __forceinline__ void epi_ab(const float (&acc)[64], const Ctx& c, float a0, float b0, float a1, float b1, uint32_t stg) {
  uint32_t w0[4], w1[4];
#pragma unroll
  for (int i = 0; i < 4; i++) {
    float2 cs = lds2f(c.sm + OFF_VAB + (32 * G + 8 * i) * 4 + (c.lane & 3) * 8);
    const int r = 4 * (4 * G + i);
    w0[i] = pack2(fmaf(a0, acc[r], b0 * cs.x), fmaf(a0, acc[r + 1], b0 * cs.y));
    w1[i] = pack2(fmaf(a1, acc[r + 2], b1 * cs.x), fmaf(a1, acc[r + 3], b1 * cs.y));
  }
  sts4(stg + G * 8192, w0[0], w0[1], w0[2], w0[3]);
  sts4(stg + G * 8192 + 512, w1[0], w1[1], w1[2], w1[3]);
}
template <int G, int VG, int NA>
__device__ __forceinline__ void epi_h(const float (&acc)[NA], const Ctx& c, float a0, float b0, float a1, float b1, uint32_t stg) {
  uint32_t w0[4], w1[4];
#pragma unroll
  for (int i = 0; i < 4; i++) {
    float4 v = lds4f(c.sm + OFF_VH + (16 * VG + 4 * i) * 16 + (c.lane & 3) * 16);
    const int r = 4 * (4 * G + i);
    w0[i] = pack2(gelu_f(fmaf(a0, acc[r], fmaf(b0, v.x, v.z))), gelu_f(fmaf(a0, acc[r + 1], fmaf(b0, v.y, v.w))));
    w1[i] = pack2(gelu_f(fmaf(a1, acc[r + 2], fmaf(b1, v.x, v.z))), gelu_f(fmaf(a1, acc[r + 3], fmaf(b1, v.y, v.w))));
  }
  sts4(stg + G * 8192, w0[0], w0[1], w0[2], w0[3]);
  sts4(stg + G * 8192 + 512, w1[0], w1[1], w1[2], w1[3]);
}
template <int G>
__device__ __forceinline__ void epi_g(const float (&acc)[64], const Ctx& c, uint32_t stg, uint4& o0, uint4& o1) {
  uint32_t w0[4], w1[4];
#pragma unroll
  for (int i = 0; i < 4; i++) {
    uint32_t bw; asm volatile("ld.shared.u32 %0, [%1];" : "=r"(bw) : "r"(c.sm + OFF_B2 + (32 * G + 8 * i) * 2 + (c.lane & 3) * 4));
    const float2 b = make_float2(bf_lo(bw), bf_hi(bw));
    const int r = 4 * (4 * G + i);
    w0[i] = pack2(silu_f(acc[r] + b.x), silu_f(acc[r + 1] + b.y));
    w1[i] = pack2(silu_f(acc[r + 2] + b.x), silu_f(acc[r + 3] + b.y));
  }
  const int r8 = c.lane & 7, mi = c.lane >> 3;
  const uint32_t wa = stg + r8 * 128 + ((((G & 1) * 4 + mi) ^ r8) << 4);
  __syncwarp();
  asm volatile("stmatrix.sync.aligned.m8n8.x4.shared.b16 [%0], {%1,%2,%3,%4};" :: "r"(wa), "r"(w0[0]), "r"(w0[1]), "r"(w0[2]), "r"(w0[3]) : "memory");
  asm volatile("stmatrix.sync.aligned.m8n8.x4.shared.b16 [%0], {%1,%2,%3,%4};" :: "r"(wa + 1024), "r"(w1[0]), "r"(w1[1]), "r"(w1[2]), "r"(w1[3]) : "memory");
  __syncwarp();
  const int rr = c.lane >> 2;
  const uint32_t ra = stg + rr * 128 + ((((G & 1) * 4 + (c.lane & 3)) ^ rr) << 4);
  o0 = lds4u(ra);
  o1 = lds4u(ra + 1024);
}

template <int ROLE>
__device__ __forceinline__ void tail(float (&y)[64], float (&m)[64], const Ctx& c, const Params& p, int tid, size_t ooff) {
  const uint32_t peer = ROLE ^ 1;
  uint4 g[4], xr[4];
  const uint32_t stg = c.sm + OFF_G + (tid >> 5) * 2048;
  const uint32_t rg = mapa(c.sm + OFF_G + tid * 16, peer), rgb = mapa(c.sm + OFF_BAR + BAR_G, peer);
#pragma unroll
  for (int s = NSTEPS - 6; s < NSTEPS; s++) {
    mma_step<128, 1>(y, c, s % NST, (s / NST) & 1, 1);
    wg_wait<1>();
    if (s == NSTEPS - 6) {
      release(c, (s - 1) % NST);
      asm volatile("barrier.cluster.wait.aligned;" ::: "memory");
      if (ROLE == 1) reg_fence(m);
    }
    if (s == NSTEPS - 5 && c.lane == 0) mbar_arrive_cluster(mapa(c.sm + OFF_BAR + BAR_OK, peer));
    if (ROLE == 1) {
      if (s == NSTEPS - 6) { uint4 t0, t1; epi_g<0>(m, c, stg, t0, t1); st_async4(rg, t0.x, t0.y, t0.z, t0.w, rgb); st_async4(rg + 4096, t1.x, t1.y, t1.z, t1.w, rgb); }
      if (s == NSTEPS - 5) { uint4 t0, t1; epi_g<1>(m, c, stg, t0, t1); st_async4(rg + 8192, t0.x, t0.y, t0.z, t0.w, rgb); st_async4(rg + 12288, t1.x, t1.y, t1.z, t1.w, rgb); }
      if (s == NSTEPS - 4) epi_g<2>(m, c, stg, g[0], g[1]);
      if (s == NSTEPS - 3) epi_g<3>(m, c, stg, g[2], g[3]);
    }
    if (s == NSTEPS - 3) {
      xr[0] = ldg_nc(p.x + ooff); xr[1] = ldg_nc(p.x + ooff + 8 * DM);
      xr[2] = ldg_nc(p.x + ooff + 32); xr[3] = ldg_nc(p.x + ooff + 8 * DM + 32);
    }
  }
  if (ROLE == 0) {
    mbar_wait(c.sm + OFF_BAR + BAR_G, 0);
#pragma unroll
    for (int v = 0; v < 4; v++) g[v] = lds4u(c.sm + OFF_G + v * 4096 + tid * 16);
  }
  mbar_wait(c.sm + OFF_BAR + BAR_OK, 0);
  const uint32_t rl = mapa(c.sm + LAND_STAGE * STB + tid * 16, peer), rlb = mapa(c.sm + OFF_BAR + BAR_Y, peer);
  wg_wait<0>();
  reg_fence(y);
  TLC(8);
  constexpr int SND = ROLE == 0 ? 32 : 0, KEEP = 32 - SND;
#pragma unroll
  for (int v = 0; v < 8; v++)
    st_async4(rl + v * 4096, __float_as_uint(y[SND + 4 * v]), __float_as_uint(y[SND + 4 * v + 1]), __float_as_uint(y[SND + 4 * v + 2]), __float_as_uint(y[SND + 4 * v + 3]), rlb);
  mbar_wait(c.sm + OFF_BAR + BAR_Y, 0);
  TLC(9);
#pragma unroll
  for (int G = 0; G < 2; G++) {
    float4 r[4];
#pragma unroll
    for (int i = 0; i < 4; i++) {
      uint4 t = lds4u(c.sm + LAND_STAGE * STB + (4 * G + i) * 4096 + tid * 16);
      r[i] = make_float4(__uint_as_float(t.x), __uint_as_float(t.y), __uint_as_float(t.z), __uint_as_float(t.w));
    }
    uint32_t o0[4], o1[4];
    const uint32_t g0[4] = {g[2 * G].x, g[2 * G].y, g[2 * G].z, g[2 * G].w}, g1[4] = {g[2 * G + 1].x, g[2 * G + 1].y, g[2 * G + 1].z, g[2 * G + 1].w};
    const uint32_t x0[4] = {xr[2 * G].x, xr[2 * G].y, xr[2 * G].z, xr[2 * G].w}, x1[4] = {xr[2 * G + 1].x, xr[2 * G + 1].y, xr[2 * G + 1].z, xr[2 * G + 1].w};
#pragma unroll
    for (int i = 0; i < 4; i++) {
      const int a = KEEP + 4 * (4 * G + i);
      o0[i] = pack2(fmaf(y[a] + r[i].x, bf_lo(g0[i]), bf_lo(x0[i])), fmaf(y[a + 1] + r[i].y, bf_hi(g0[i]), bf_hi(x0[i])));
      o1[i] = pack2(fmaf(y[a + 2] + r[i].z, bf_lo(g1[i]), bf_lo(x1[i])), fmaf(y[a + 3] + r[i].w, bf_hi(g1[i]), bf_hi(x1[i])));
    }
    stg4(p.out + ooff + 32 * G, o0[0], o0[1], o0[2], o0[3]);
    stg4(p.out + ooff + 32 * G + 8 * DM, o1[0], o1[1], o1[2], o1[3]);
  }
  TLC(10);
}

__global__ void __cluster_dims__(2, 1, 1) __launch_bounds__(384, 1) fused_kernel(const __grid_constant__ Params p) {
  extern __shared__ __align__(1024) uint8_t smem_raw[];
  const uint32_t sm = (uint32_t)__cvta_generic_to_shared(smem_raw);
  const int tid = threadIdx.x, lane = tid & 31;
  const int warp = __shfl_sync(0xffffffffu, tid >> 5, 0);
  int lc;
  {
    const int c = blockIdx.x >> 1;
    if (c < 4) lc = 4 + c;
    else if (c < 36) lc = ((c - 4) & 7) * 8 + ((c - 4) >> 3);
    else lc = (1 + (c - 36) % 7) * 8 + 4 + (c - 36) / 7;
  }
  const int role = blockIdx.x & 1, cb = lc & 3, rb = lc >> 2, j = cb * 2 + role, lb = lc * 2 + role;
  const uint32_t bars = sm + OFF_BAR;
  TLC(0);
#define EPOCH() mbar_wait(bars + BAR_E, 0); unsigned epoch; asm volatile("ld.shared.u32 %0, [%1];" : "=r"(epoch) : "r"(bars + OFF_EPOCH) : "memory"); const uint32_t tag = epoch & 3
  if (warp >= 8) {
    asm volatile("setmaxnreg.dec.sync.aligned.u32 120;");
    if (warp == 8) {
      {
        if (elect_one()) {
          for (int s = 0; s < 8; s++) mbar_init(bars + BAR_XF + 8 * s, 1);
          for (int s = 0; s < 4; s++) { mbar_init(bars + BAR_BF + 8 * s, 1); mbar_init(bars + BAR_BE + 8 * s, 8); }
          fence_async_smem();
          const CUtensorMap* md = j < 4 ? &p.mdre : &p.mdim;
          for (int k = 0; k < 8; k++) {
            mbar_expect_tx(bars + BAR_XF + 8 * k, 16384);
            tma2d(sm + xslot(k), &p.mx, k * 64, rb * 128, bars + BAR_XF + 8 * k);
            if (k < 4) {
              mbar_expect_tx(bars + BAR_BF + 8 * k, 16384);
              tma2d(sm + bslot(k), md, k * 64, (j & 3) * 128, bars + BAR_BF + 8 * k);
            }
          }
          for (int s = 0; s < NST; s++) { mbar_init(bars + BAR_FULL + 8 * s, 1); mbar_init(bars + BAR_EMPTY + 8 * s, 8); }
          mbar_init(bars + BAR_V1, 1); mbar_init(bars + BAR_V2, 2); mbar_init(bars + BAR_FREE, 1); mbar_init(bars + BAR_E, 1);
          mbar_init(bars + BAR_G, 1); mbar_init(bars + BAR_Y, 1); mbar_init(bars + BAR_OK, 8);
          asm volatile("fence.mbarrier_init.release.cluster;" ::: "memory");
          fence_async_smem();
          mbar_expect_tx(bars + BAR_G, 16384);
          mbar_expect_tx(bars + BAR_Y, 32768);
        }
        __syncwarp();
      }
      __syncthreads();
      asm volatile("barrier.cluster.arrive.relaxed.aligned;" ::: "memory");
      if (elect_one()) {
        asm volatile("prefetch.tensormap [%0];" :: "l"(&p.mw1) : "memory");
        asm volatile("prefetch.tensormap [%0];" :: "l"(&p.mcr) : "memory");
        asm volatile("prefetch.tensormap [%0];" :: "l"(&p.mci) : "memory");
        asm volatile("prefetch.tensormap [%0];" :: "l"(&p.mab) : "memory");
        if (role) {
          asm volatile("prefetch.tensormap [%0];" :: "l"(&p.mh) : "memory");
          asm volatile("prefetch.tensormap [%0];" :: "l"(&p.mw2) : "memory");
        }
        int st = 0; uint32_t ph = 0;
        const int y0 = role ? 46 : 0;
        const int row0 = rb * 128;
#define P_ACQ() mbar_wait(bars + BAR_EMPTY + 8 * st, ph); const uint32_t fb = bars + BAR_FULL + 8 * st, sa = sm + st * STB, sb = sa + 16384; mbar_expect_tx(fb, STB)
#define P_ADV() if (++st == NST) { st = 0; ph ^= 1; }
        const CUtensorMap* md = j < 4 ? &p.mdre : &p.mdim;
        for (int k = 4; k < 24; k++) {
          const uint32_t fb = bars + BAR_BF + 8 * (k & 3), sb = sm + bslot(k & 3);
          mbar_wait(bars + BAR_BE + 8 * (k & 3), ((k >> 2) & 1) ^ 1);
          mbar_expect_tx(fb, 16384);
          if (k < 8) tma2d(sb, md, k * 64, (j & 3) * 128, fb);
          else tma3d(sb, &p.mw1, j * 224 + (k >> 4) * 96, (k & 7) * 64, 0, fb);
        }
        TLREC(11);
        EPOCH();
        if (!role) wait_cnt(&g_cnt[C_AB + cb * 32], 16 * epoch);
        wait_cnt(&g_cnt[C_AB + (4 + cb) * 32], 16 * epoch);
        asm volatile("fence.proxy.async.global;" ::: "memory");
        TLREC(12);
        const int nya = role ? 18 - NYB : 46;
        for (int k = y0; k < y0 + nya; k++) {
          P_ACQ(); tma2d(sa, k < 32 ? &p.mcr : &p.mci, (k & 31) * 64, row0, fb); tma3d(sb, &p.mab, 0, k * 64, cb * 2, fb); P_ADV();
        }
        if (role) {
          TLREC(13);
          wait_cnt(&g_cnt[C_H + rb * 32], 16 * epoch);
          asm volatile("fence.proxy.async.global;" ::: "memory");
          TLREC(14);
          for (int k = 0; k < 28; k++) {
            P_ACQ(); tma2d(sa, &p.mh, k * 64, row0, fb); tma5d(sb, &p.mw2, cb * 128, 2 * k, fb); tma5d(sb + 8192, &p.mw2, cb * 128 + 64, 2 * k, fb); P_ADV();
          }
          for (int k = 64 - NYB; k < 64; k++) {
            P_ACQ(); tma2d(sa, &p.mci, (k & 31) * 64, row0, fb); tma3d(sb, &p.mab, 0, k * 64, cb * 2, fb); P_ADV();
          }
        }
        red_add(&g_cnt[C_DONE]);
      }
    } else if (warp == 9) {
      unsigned done0 = 0;
      if (lane == 0) done0 = ld_rlx(&g_cnt[C_DONE]);
      const int d0 = lb * 8;
      const __nv_bfloat16* d = (d0 < DM ? p.dre + (size_t)d0 * DM : p.dim + (size_t)(d0 - DM) * DM) + lane * 8;
      __syncthreads();
      asm volatile("barrier.cluster.arrive.relaxed.aligned;" ::: "memory");
      mbar_wait(bars + BAR_XF + 8 * DLY_D, 0);
      uint4 u[8][2];
#pragma unroll
      for (int r = 0; r < 8; r++) { u[r][0] = ldg_nc(d + r * DM); u[r][1] = ldg_nc(d + r * DM + 256); }
      if (lane == 0) { asm volatile("st.shared.u32 [%0], %1;" :: "r"(bars + OFF_EPOCH), "r"((done0 >> 7) + 1) : "memory"); mbar_arrive(bars + BAR_E); TLREC(23); }
      __syncwarp();
      EPOCH();
      float t[8];
#pragma unroll
      for (int r = 0; r < 8; r++) t[r] = sum8(u[r][0]) + sum8(u[r][1]);
#pragma unroll
      for (int o = 4; o > 0; o >>= 1) {
#pragma unroll
        for (int r = 0; r < o; r++) {
          const bool up = lane & o;
          const float keep = up ? t[r + o] : t[r], give = up ? t[r] : t[r + o];
          t[r] = keep + __shfl_xor_sync(0xffffffffu, give, o);
        }
      }
      t[0] += __shfl_xor_sync(0xffffffffu, t[0], 8);
      t[0] += __shfl_xor_sync(0xffffffffu, t[0], 16);
      if (lane < 8) asm volatile("st.relaxed.gpu.global.u32 [%0], %1;" :: "l"(&g_cs[d0 + lane]), "r"(tagf(t[0], tag)) : "memory");
      if (lane == 0) TLREC(15);
      uint4 cv;
      { uint32_t n = 0; do { cv = ld_msg(&g_cs[j * 128 + lane * 4]); if (++n > (1u << 20)) __trap(); } while (__any_sync(0xffffffffu, stale(cv, tag))); }
      sts4(sm + OFF_VAB + lane * 16, cv.x, cv.y, cv.z, cv.w);
      __syncwarp();
      if (lane == 0) { mbar_arrive(bars + BAR_V1); TLREC(16); }
      if (lane == 0) { asm volatile("prefetch.tensormap [%0];" :: "l"(&p.sab) : "memory"); asm volatile("prefetch.tensormap [%0];" :: "l"(&p.sh) : "memory"); }
      for (int tile = 0; tile < 3; tile++) {
        bar_sync(1 + tile, 288);
        if (elect_one()) {
          TLREC(25 + tile);
          const CUtensorMap* m = tile ? &p.sh : &p.sab;
          const int c0 = tile == 0 ? (j & 3) * 128 : j * 224 + (tile - 1) * 96, r0 = (tile == 0 ? (j >> 2) * SEQ : 0) + rb * 128;
          for (int g = 0; g < (tile == 1 ? 3 : 4); g++) tma_st2d(m, sm + OFF_STG + g * 8192, c0 + g * 32, r0);
          asm volatile("cp.async.bulk.commit_group;\ncp.async.bulk.wait_group 0;" ::: "memory");
          red_add(tile ? &g_cnt[C_H + rb * 32] : &g_cnt[C_AB + j * 32]);
          mbar_arrive(bars + BAR_FREE);
          TLREC(17 + tile);
        }
        __syncwarp();
      }
    } else {
      const int cl = lane < 28 ? lane : 27;
      const __nv_bfloat16* w = p.w1 + (size_t)(rb * 32 + (warp - 10) * 16) * FF + j * 224 + cl * 8;
      __syncthreads();
      asm volatile("barrier.cluster.arrive.relaxed.aligned;" ::: "memory");
      uint4 v[16];
      {
        const int r = j * 16 + (warp - 10) * 8 + (lane >> 2);
        const uint32_t rowa = sm + r * 128, c0 = (((lane & 3) * 2) ^ (r & 7)) << 4;
        float piv = 0.f, sa = 0.f, sb = 0.f, qa = 0.f, qb = 0.f;
#pragma unroll 1
        for (int k = 0; k < 8; k++) {
          mbar_wait(bars + BAR_XF + 8 * k, 0);
          if (k == 0) { uint32_t t; asm volatile("ld.shared.u32 %0, [%1];" : "=r"(t) : "r"(rowa + ((r & 7) << 4)) : "memory"); piv = bf_lo(t); }
          if (k == DLY_W) {
#pragma unroll
            for (int i = 0; i < 16; i++) v[i] = ldg_nc(w + (size_t)i * FF);
          }
          const uint4 t0 = lds4u(rowa + xslot(k) + c0), t1 = lds4u(rowa + xslot(k) + (c0 ^ 16));
          const uint32_t ww[8] = {t0.x, t0.y, t0.z, t0.w, t1.x, t1.y, t1.z, t1.w};
#pragma unroll
          for (int i = 0; i < 8; i++) {
            const float a = bf_lo(ww[i]) - piv, b = bf_hi(ww[i]) - piv;
            sa += a; sb += b; qa = fmaf(a, a, qa); qb = fmaf(b, b, qb);
          }
        }
        float s1 = sa + sb, s2 = qa + qb;
        s1 += __shfl_xor_sync(0xffffffffu, s1, 1); s2 += __shfl_xor_sync(0xffffffffu, s2, 1);
        s1 += __shfl_xor_sync(0xffffffffu, s1, 2); s2 += __shfl_xor_sync(0xffffffffu, s2, 2);
        s1 *= 1.0f / DM;
        const float mean = piv + s1, var = fmaxf(fmaf(s2, 1.0f / DM, -s1 * s1), 0.f);
        const float m1 = bfr(mean), d1 = bfr(__fsqrt_rn(bfr(bfr(var) + 1e-5f))), i1 = __frcp_rn(d1);
        const float m2 = bfr((mean - m1) * i1), d2 = bfr(__fsqrt_rn(bfr(bfr(var * i1 * i1) + 1e-5f))), i2 = __frcp_rn(d2);
        EPOCH();
        if ((lane & 3) == 0) st_msg(&g_stats[rb * 128 + r], tagf(i1, tag), tagf(-m1 * i1, tag), tagf(i1 * i2, tag), tagf(-(m1 * i1 + m2) * i2, tag));
        if (warp == 10 && lane == 0) TLREC(20);
      }
      float s[8] = {0.f, 0.f, 0.f, 0.f, 0.f, 0.f, 0.f, 0.f};
#pragma unroll
      for (int r = 0; r < 16; r++) {
        s[0] += bf_lo(v[r].x); s[1] += bf_hi(v[r].x); s[2] += bf_lo(v[r].y); s[3] += bf_hi(v[r].y);
        s[4] += bf_lo(v[r].z); s[5] += bf_hi(v[r].z); s[6] += bf_lo(v[r].w); s[7] += bf_hi(v[r].w);
      }
      EPOCH();
      float4* s4 = reinterpret_cast<float4*>(smem_raw);
      if (warp == 11) {
        if (lane < 28) { s4[OFF_VH / 16 + lane * 2] = make_float4(s[0], s[1], s[2], s[3]); s4[OFF_VH / 16 + lane * 2 + 1] = make_float4(s[4], s[5], s[6], s[7]); }
        const uint2 b2v = *reinterpret_cast<const uint2*>(p.b2 + cb * 128 + lane * 4);
        reinterpret_cast<uint2*>(smem_raw + OFF_B2)[lane] = b2v;
      }
      bar_sync(4, 64);
      if (warp == 10 && lane < 28) {
        const float4 o0 = s4[OFF_VH / 16 + lane * 2], o1 = s4[OFF_VH / 16 + lane * 2 + 1];
        float* dst = &g_csw[rb * FF + j * 224 + lane * 8];
        st_msg(dst, tagf(s[0] + o0.x, tag), tagf(s[1] + o0.y, tag), tagf(s[2] + o0.z, tag), tagf(s[3] + o0.w, tag));
        st_msg(dst + 4, tagf(s[4] + o1.x, tag), tagf(s[5] + o1.y, tag), tagf(s[6] + o1.z, tag), tagf(s[7] + o1.w, tag));
      }
      bar_sync(4, 64);
      const int q = (warp - 10) * 28 + cl;
      const uint2 bb = *reinterpret_cast<const uint2*>(p.b1 + j * 224 + q * 4);
      float4 acc;
      uint32_t n = 0, bad;
      do {
        uint4 m[16];
#pragma unroll
        for (int r = 0; r < 16; r++) m[r] = ld_msg(&g_csw[r * FF + j * 224 + q * 4]);
        acc = make_float4(0.f, 0.f, 0.f, 0.f); bad = 0;
#pragma unroll
        for (int r = 0; r < 16; r++) {
          bad |= stale(m[r], tag);
          acc.x += __uint_as_float(m[r].x); acc.y += __uint_as_float(m[r].y); acc.z += __uint_as_float(m[r].z); acc.w += __uint_as_float(m[r].w);
        }
        if (++n > (1u << 20)) __trap();
      } while (__any_sync(0xffffffffu, bad));
      if (lane < 28) {
        s4[OFF_VH / 16 + q * 2] = make_float4(acc.x, acc.y, bf_lo(bb.x), bf_hi(bb.x));
        s4[OFF_VH / 16 + q * 2 + 1] = make_float4(acc.z, acc.w, bf_lo(bb.y), bf_hi(bb.y));
      }
      __syncwarp();
      if (lane == 0) { mbar_arrive(bars + BAR_V2); if (warp == 10) TLREC(24); }
    }
  } else {
    asm volatile("setmaxnreg.inc.sync.aligned.u32 192;");
    __syncthreads();
    asm volatile("barrier.cluster.arrive.relaxed.aligned;" ::: "memory");
    Ctx c; c.sm = sm; c.lane = lane;
    c.da = (((sm + (warp >> 2) * 8192) & 0x3FFFF) >> 4) | (1u << 16); c.db = ((sm + 16384) & 0x3FFFF) >> 4;
    const int rl = warp * 16 + (lane >> 2);
    const int q8 = (lane & 3) * 8;
    const uint32_t stg = sm + OFF_STG + rl * 64 + (lane & 3) * 16;
    float P[64], Q[48], R[64], Y[64], M[64];
    static_for<0, 8>([&](auto S_) {
      constexpr int S = decltype(S_)::value;
      mma_step1<128, 0, S>(P, c);
      if (S == 0) TLC(1);
      if constexpr (S > 0) { wg_wait<1>(); release1<S - 1>(c); }
    });
    TLC(2);
    EPOCH();
    uint4 m0, m1;
    float4 s0, s1;
    static_for<8, 16>([&](auto S_) {
      constexpr int S = decltype(S_)::value;
      mma_step1<96, 1, S>(Q, c);
      if (S == 8) { m0 = ld_msg(&g_stats[rb * 128 + rl]); m1 = ld_msg(&g_stats[rb * 128 + rl + 8]); }
      wg_wait<1>();
      release1<S - 1>(c);
      if (S == 9) {
        reg_fence(P);
        uint32_t n = 0;
        while (stale(m0, tag) | stale(m1, tag)) { m0 = ld_msg(&g_stats[rb * 128 + rl]); m1 = ld_msg(&g_stats[rb * 128 + rl + 8]); if (++n > (1u << 20)) __trap(); }
        const float sg = j < 4 ? 1.f : -1.f;
        s0 = make_float4(__uint_as_float(m0.x) * sg, __uint_as_float(m0.y) * sg, __uint_as_float(m0.z), __uint_as_float(m0.w));
        s1 = make_float4(__uint_as_float(m1.x) * sg, __uint_as_float(m1.y) * sg, __uint_as_float(m1.z), __uint_as_float(m1.w));
        mbar_wait(bars + BAR_V1, 0);
        TLC(21);
        epi_ab<0>(P, c, s0.x, s0.y, s1.x, s1.y, stg);
        epi_ab<1>(P, c, s0.x, s0.y, s1.x, s1.y, stg);
      }
      if (S == 10) {
        epi_ab<2>(P, c, s0.x, s0.y, s1.x, s1.y, stg);
        epi_ab<3>(P, c, s0.x, s0.y, s1.x, s1.y, stg);
        fence_async_smem();
        bar_arrive(1, 288);
      }
    });
    TLC(3);
    static_for<16, 24>([&](auto S_) {
      constexpr int S = decltype(S_)::value;
      mma_step1<128, 1, S>(R, c);
      wg_wait<1>();
      release1<S - 1>(c);
      if (S == 16) { reg_fence(Q); mbar_wait(bars + BAR_V2, 0); mbar_wait(bars + BAR_FREE, 0); epi_h<0, 0>(Q, c, s0.z, s0.w, s1.z, s1.w, stg); }
      if (S == 18) epi_h<1, 1>(Q, c, s0.z, s0.w, s1.z, s1.w, stg);
      if (S == 20) { epi_h<2, 2>(Q, c, s0.z, s0.w, s1.z, s1.w, stg); fence_async_smem(); bar_arrive(2, 288); }
    });
    TLC(4);
#pragma unroll
    for (int s = 24; s < 30; s++) {
      mma_step<128, 1>(Y, c, s % NST, (s / NST) & 1, s > 24);
      wg_wait<1>();
      release(c, (s - 1) % NST);
      if (s == 24) { reg_fence(R); mbar_wait(bars + BAR_FREE, 1); epi_h<0, 3>(R, c, s0.z, s0.w, s1.z, s1.w, stg); }
      if (s == 25) epi_h<1, 4>(R, c, s0.z, s0.w, s1.z, s1.w, stg);
      if (s == 26) epi_h<2, 5>(R, c, s0.z, s0.w, s1.z, s1.w, stg);
      if (s == 27) { epi_h<3, 6>(R, c, s0.z, s0.w, s1.z, s1.w, stg); fence_async_smem(); bar_arrive(3, 288); }
    }
    TLC(5);
    int st = 30 % NST, pst = 29 % NST; uint32_t ph = (30 / NST) & 1;
    const int ny = role ? 12 - NYB : 40 - NYB;
    for (int k = 0; k < ny; k++) {
      mma_step<128, 1>(Y, c, st, ph, 1);
      wg_wait<1>();
      release(c, pst);
      pst = st; if (++st == NST) { st = 0; ph ^= 1; }
    }
    TLC(6);
    const size_t ooff = (size_t)(rb * 128 + rl) * DM + cb * 128 + role * 64 + q8;
    if (role) {
      for (int k = 0; k < 28; k++) {
        mma_step<128, 1>(M, c, st, ph, k);
        wg_wait<1>();
        release(c, pst);
        pst = st; if (++st == NST) { st = 0; ph ^= 1; }
      }
      TLC(7);
      tail<1>(Y, M, c, p, tid, ooff);
    } else {
      TLC(7);
      tail<0>(Y, M, c, p, tid, ooff);
    }
  }
}

typedef CUresult (*EncFn)(CUtensorMap*, CUtensorMapDataType, cuuint32_t, void*, const cuuint64_t*, const cuuint64_t*, const cuuint32_t*,
                          const cuuint32_t*, CUtensorMapInterleave, CUtensorMapSwizzle, CUtensorMapL2promotion, CUtensorMapFloatOOBfill);

void make_map(EncFn enc, CUtensorMap* m, const void* ptr, int nd, const uint64_t* dims, const uint64_t* strides, const uint32_t* box,
              CUtensorMapSwizzle sw = CU_TENSOR_MAP_SWIZZLE_128B) {
  const cuuint32_t es[5] = {1, 1, 1, 1, 1};
  cuuint64_t d[5], s[5]; cuuint32_t b[5];
  for (int i = 0; i < nd; i++) { d[i] = dims[i]; b[i] = box[i]; if (i + 1 < nd) s[i] = strides[i]; }
  enc(m, CU_TENSOR_MAP_DATA_TYPE_BFLOAT16, nd, const_cast<void*>(ptr), d, s, b, es, CU_TENSOR_MAP_INTERLEAVE_NONE,
      sw, CU_TENSOR_MAP_L2_PROMOTION_L2_128B, CU_TENSOR_MAP_FLOAT_OOB_FILL_NONE);
}

}

extern "C" void kernel_launch(void* const* d_in, const int* in_sizes, int n_in, void* d_out, int out_size) {
  static Params prm;
  static const void* key[11];
  static EncFn enc = nullptr;
  bool same = enc != nullptr && key[10] == d_out;
  for (int i = 0; i < 10 && same; i++) same = key[i] == d_in[i];
  if (!same) {
    if (!enc) {
      cudaDriverEntryPointQueryResult q;
      cudaGetDriverEntryPoint("cuTensorMapEncodeTiled", reinterpret_cast<void**>(&enc), cudaEnableDefault, &q);
      cudaFuncSetAttribute(fused_kernel, cudaFuncAttributeMaxDynamicSharedMemorySize, SMEM_BYTES);
    }
    void *ab, *h;
    cudaGetSymbolAddress(&ab, g_ab);
    cudaGetSymbolAddress(&h, g_h);
    const uint32_t box2[2] = {64, 128}, box3[3] = {64, 64, 2}, box5[5] = {64, 2, 4, 4, 2};
    { const uint64_t d[2] = {DM, SEQ}, s[1] = {DM * 2}; make_map(enc, &prm.mx, d_in[0], 2, d, s, box2); }
    { const uint64_t d[2] = {SEQ, SEQ}, s[1] = {SEQ * 2}; make_map(enc, &prm.mcr, d_in[1], 2, d, s, box2); make_map(enc, &prm.mci, d_in[2], 2, d, s, box2); }
    { const uint64_t d[2] = {DM, DM}, s[1] = {DM * 2}; make_map(enc, &prm.mdre, d_in[3], 2, d, s, box2); make_map(enc, &prm.mdim, d_in[4], 2, d, s, box2); }
    { const uint64_t d[3] = {FF, DM, 2}, s[2] = {FF * 2, 128}; make_map(enc, &prm.mw1, d_in[6], 3, d, s, box3); }
    { const uint64_t d[3] = {64, 2 * SEQ, 8}, s[2] = {DM * 2, 128}; make_map(enc, &prm.mab, ab, 3, d, s, box3); }
    { const uint64_t d[2] = {FF, SEQ}, s[1] = {FF * 2}; make_map(enc, &prm.mh, h, 2, d, s, box2); }
    { const uint64_t d[5] = {DM, 2, 4, 4, FF / 32}, s[4] = {DM * 2, 8 * DM * 2, 2 * DM * 2, 32 * DM * 2}; make_map(enc, &prm.mw2, d_in[8], 5, d, s, box5); }
    const uint32_t boxs[2] = {32, 128};
    { const uint64_t d[2] = {DM, 2 * SEQ}, s[1] = {DM * 2}; make_map(enc, &prm.sab, ab, 2, d, s, boxs, CU_TENSOR_MAP_SWIZZLE_NONE); }
    { const uint64_t d[2] = {FF, SEQ}, s[1] = {FF * 2}; make_map(enc, &prm.sh, h, 2, d, s, boxs, CU_TENSOR_MAP_SWIZZLE_NONE); }
    prm.x = (const __nv_bfloat16*)d_in[0]; prm.dre = (const __nv_bfloat16*)d_in[3]; prm.dim = (const __nv_bfloat16*)d_in[4];
    prm.w1 = (const __nv_bfloat16*)d_in[6]; prm.b1 = (const __nv_bfloat16*)d_in[7]; prm.w2 = (const __nv_bfloat16*)d_in[8];
    prm.b2 = (const __nv_bfloat16*)d_in[9]; prm.out = (__nv_bfloat16*)d_out;
    for (int i = 0; i < 10; i++) key[i] = d_in[i];
    key[10] = d_out;
  }
  fused_kernel<<<128, 384, SMEM_BYTES>>>(prm);
}
```

```cpp
#include <cuda_runtime.h>
#include <cuda_bf16.h>
#include <cuda.h>
#include <stdint.h>

namespace {

constexpr int SEQ = 2048, DM = 512, FF = 1792;
constexpr int NST = 6;
constexpr int STB = 32768;
constexpr int OFF_STG = NST * STB;
constexpr int OFF_G = OFF_STG;
constexpr int OFF_VAB = OFF_STG + 32768;
constexpr int OFF_VH = OFF_VAB + 512;
constexpr int OFF_B2 = OFF_VH + 1792;
constexpr int OFF_BAR = OFF_B2 + 256;
constexpr int SMEM_BYTES = OFF_BAR + 288;
static_assert(SMEM_BYTES <= 232448, "smem");
constexpr int BAR_FULL = 0, BAR_EMPTY = 48, BAR_V1 = 96, BAR_G = 104, BAR_Y = 112, BAR_OK = 120, BAR_V2 = 128, BAR_FREE = 136,
              BAR_E = 144, OFF_EPOCH = 152, BAR_XF = 160, BAR_BF = 224, BAR_BE = 256;
__host__ __device__ constexpr int xslot(int k) { return (k < 4 ? k : 2 * k - 4) * 16384; }
__host__ __device__ constexpr int bslot(int i) { return (5 + 2 * i) * 16384; }
#define INIT_X 8
#define AB0 10
#define HA0 19
#define HA1 20
#define HA2 21
#define HB0 24
#define NYB_ 4
#define DLY_D 0
#define DLY_W 3
constexpr int NSTEPS = 70;
constexpr int NYB = NYB_;
constexpr int LAND_STAGE = (NSTEPS - NYB) % NST;

constexpr int C_DONE = 0, C_AB = 64, C_H = 64 + 8 * 32;

struct Params {
  CUtensorMap mx, mdre, mdim, mw1, mcr, mci, mab, mh, mw2, sab, sh;
  const __nv_bfloat16 *x, *dre, *dim, *w1, *b1, *w2, *b2;
  __nv_bfloat16* out;
};

__device__ __align__(1024) __nv_bfloat16 g_ab[2 * SEQ * DM];
__device__ __align__(1024) __nv_bfloat16 g_h[SEQ * FF];
__device__ float4 g_stats[SEQ];
__device__ __align__(16) float g_cs[2 * DM];
__device__ __align__(16) float g_csw[16 * FF];
__device__ unsigned g_cnt[64 + 8 * 32 + 16 * 32];
#define TLREC(ev) do {} while (0)
#define TLC(ev) do {} while (0)

__device__ __forceinline__ void mbar_init(uint32_t bar, uint32_t cnt) { asm volatile("mbarrier.init.shared::cta.b64 [%0], %1;" :: "r"(bar), "r"(cnt) : "memory"); }
__device__ __forceinline__ void mbar_expect_tx(uint32_t bar, uint32_t bytes) { asm volatile("mbarrier.arrive.expect_tx.shared::cta.b64 _, [%0], %1;" :: "r"(bar), "r"(bytes) : "memory"); }
__device__ __forceinline__ void mbar_arrive(uint32_t bar) { asm volatile("mbarrier.arrive.shared::cta.b64 _, [%0];" :: "r"(bar) : "memory"); }
__device__ __forceinline__ void mbar_arrive_cluster(uint32_t remote_bar) { asm volatile("mbarrier.arrive.shared::cluster.b64 _, [%0];" :: "r"(remote_bar) : "memory"); }
__device__ __forceinline__ uint32_t mapa(uint32_t addr, uint32_t cta) { uint32_t r; asm("mapa.shared::cluster.u32 %0, %1, %2;" : "=r"(r) : "r"(addr), "r"(cta)); return r; }
__device__ __forceinline__ bool mbar_try(uint32_t bar, uint32_t parity) {
  uint32_t ok;
  asm volatile("{\n.reg .pred p;\nmbarrier.try_wait.parity.shared::cta.b64 p, [%1], %2;\nselp.u32 %0, 1, 0, p;\n}" : "=r"(ok) : "r"(bar), "r"(parity) : "memory");
  return ok;
}
__device__ __forceinline__ void mbar_wait(uint32_t bar, uint32_t parity) {
  if (mbar_try(bar, parity)) return;
  uint32_t n = 0;
  while (!mbar_try(bar, parity)) { if (++n > (1u << 20)) __trap(); }
}
__device__ __forceinline__ bool elect_one() {
  uint32_t p;
  asm volatile("{\n.reg .pred p;\nelect.sync _|p, 0xffffffff;\nselp.u32 %0, 1, 0, p;\n}" : "=r"(p));
  return p;
}
__device__ __forceinline__ void tma2d(uint32_t dst, const CUtensorMap* m, int c0, int c1, uint32_t bar) {
  asm volatile("cp.async.bulk.tensor.2d.shared::cluster.global.mbarrier::complete_tx::bytes [%0], [%1, {%3, %4}], [%2];"
    :: "r"(dst), "l"(m), "r"(bar), "r"(c0), "r"(c1) : "memory");
}
__device__ __forceinline__ void tma3d(uint32_t dst, const CUtensorMap* m, int c0, int c1, int c2, uint32_t bar) {
  asm volatile("cp.async.bulk.tensor.3d.shared::cluster.global.mbarrier::complete_tx::bytes [%0], [%1, {%3, %4, %5}], [%2];"
    :: "r"(dst), "l"(m), "r"(bar), "r"(c0), "r"(c1), "r"(c2) : "memory");
}
__device__ __forceinline__ void tma5d(uint32_t dst, const CUtensorMap* m, int c0, int c4, uint32_t bar) {
  asm volatile("cp.async.bulk.tensor.5d.shared::cluster.global.mbarrier::complete_tx::bytes [%0], [%1, {%3, %5, %5, %5, %4}], [%2];"
    :: "r"(dst), "l"(m), "r"(bar), "r"(c0), "r"(c4), "r"(0) : "memory");
}
__device__ __forceinline__ void tma_pf2d(const CUtensorMap* m, int c0, int c1) {
  asm volatile("cp.async.bulk.prefetch.tensor.2d.L2.global [%0, {%1, %2}];" :: "l"(m), "r"(c0), "r"(c1) : "memory");
}
__device__ __forceinline__ void wg_fence() { asm volatile("wgmma.fence.sync.aligned;" ::: "memory"); }
__device__ __forceinline__ void wg_commit() { asm volatile("wgmma.commit_group.sync.aligned;" ::: "memory"); }
template <int N> __device__ __forceinline__ void wg_wait() { asm volatile("wgmma.wait_group.sync.aligned %0;" :: "n"(N) : "memory"); }
template <int N> __device__ __forceinline__ void reg_fence(float (&d)[N]) {
#pragma unroll
  for (int i = 0; i < N; i++) asm volatile("" : "+f"(d[i]) :: "memory");
}
__device__ __forceinline__ void wgmma4_n128_tb0(float (&d)[64], uint32_t a, uint32_t b, int scale_d) {
  asm volatile("{\n.reg .pred p;\n.reg .b32 la, lb, hi;\n.reg .b64 da, db;\nsetp.ne.b32 p, %66, 0;\nmov.b32 hi, 0x40000040;\n"
    "add.u32 la, %64, 0;\nadd.u32 lb, %65, 0;\nmov.b64 da, {la, hi};\nmov.b64 db, {lb, hi};\n"
    "wgmma.mma_async.sync.aligned.m64n128k16.f32.bf16.bf16 "
    "{%0, %1, %2, %3, %4, %5, %6, %7, %8, %9, %10, %11, %12, %13, %14, %15, %16, %17, %18, %19, %20, %21, %22, %23, %24, %25, %26, %27, %28, %29, %30, %31, %32, %33, %34, %35, %36, %37, %38, %39, %40, %41, %42, %43, %44, %45, %46, %47, %48, %49, %50, %51, %52, %53, %54, %55, %56, %57, %58, %59, %60, %61, %62, %63}, "
    "da, db, p, 1, 1, 0, 0;\n"
    "add.u32 la, %64, 2;\nadd.u32 lb, %65, 2;\nmov.b64 da, {la, hi};\nmov.b64 db, {lb, hi};\n"
    "wgmma.mma_async.sync.aligned.m64n128k16.f32.bf16.bf16 "
    "{%0, %1, %2, %3, %4, %5, %6, %7, %8, %9, %10, %11, %12, %13, %14, %15, %16, %17, %18, %19, %20, %21, %22, %23, %24, %25, %26, %27, %28, %29, %30, %31, %32, %33, %34, %35, %36, %37, %38, %39, %40, %41, %42, %43, %44, %45, %46, %47, %48, %49, %50, %51, %52, %53, %54, %55, %56, %57, %58, %59, %60, %61, %62, %63}, "
    "da, db, 1, 1, 1, 0, 0;\n"
    "add.u32 la, %64, 4;\nadd.u32 lb, %65, 4;\nmov.b64 da, {la, hi};\nmov.b64 db, {lb, hi};\n"
    "wgmma.mma_async.sync.aligned.m64n128k16.f32.bf16.bf16 "
    "{%0, %1, %2, %3, %4, %5, %6, %7, %8, %9, %10, %11, %12, %13, %14, %15, %16, %17, %18, %19, %20, %21, %22, %23, %24, %25, %26, %27, %28, %29, %30, %31, %32, %33, %34, %35, %36, %37, %38, %39, %40, %41, %42, %43, %44, %45, %46, %47, %48, %49, %50, %51, %52, %53, %54, %55, %56, %57, %58, %59, %60, %61, %62, %63}, "
    "da, db, 1, 1, 1, 0, 0;\n"
    "add.u32 la, %64, 6;\nadd.u32 lb, %65, 6;\nmov.b64 da, {la, hi};\nmov.b64 db, {lb, hi};\n"
    "wgmma.mma_async.sync.aligned.m64n128k16.f32.bf16.bf16 "
    "{%0, %1, %2, %3, %4, %5, %6, %7, %8, %9, %10, %11, %12, %13, %14, %15, %16, %17, %18, %19, %20, %21, %22, %23, %24, %25, %26, %27, %28, %29, %30, %31, %32, %33, %34, %35, %36, %37, %38, %39, %40, %41, %42, %43, %44, %45, %46, %47, %48, %49, %50, %51, %52, %53, %54, %55, %56, %57, %58, %59, %60, %61, %62, %63}, "
    "da, db, 1, 1, 1, 0, 0;\n"
    "}\n"
    : "+f"(d[0]), "+f"(d[1]), "+f"(d[2]), "+f"(d[3]), "+f"(d[4]), "+f"(d[5]), "+f"(d[6]), "+f"(d[7]), "+f"(d[8]), "+f"(d[9]), "+f"(d[10]), "+f"(d[11]), "+f"(d[12]), "+f"(d[13]), "+f"(d[14]), "+f"(d[15]), "+f"(d[16]), "+f"(d[17]), "+f"(d[18]), "+f"(d[19]), "+f"(d[20]), "+f"(d[21]), "+f"(d[22]), "+f"(d[23]), "+f"(d[24]), "+f"(d[25]), "+f"(d[26]), "+f"(d[27]), "+f"(d[28]), "+f"(d[29]), "+f"(d[30]), "+f"(d[31]), "+f"(d[32]), "+f"(d[33]), "+f"(d[34]), "+f"(d[35]), "+f"(d[36]), "+f"(d[37]), "+f"(d[38]), "+f"(d[39]), "+f"(d[40]), "+f"(d[41]), "+f"(d[42]), "+f"(d[43]), "+f"(d[44]), "+f"(d[45]), "+f"(d[46]), "+f"(d[47]), "+f"(d[48]), "+f"(d[49]), "+f"(d[50]), "+f"(d[51]), "+f"(d[52]), "+f"(d[53]), "+f"(d[54]), "+f"(d[55]), "+f"(d[56]), "+f"(d[57]), "+f"(d[58]), "+f"(d[59]), "+f"(d[60]), "+f"(d[61]), "+f"(d[62]), "+f"(d[63])
    : "r"(a), "r"(b), "r"(scale_d));
}
__device__ __forceinline__ void wgmma4_n128_tb1(float (&d)[64], uint32_t a, uint32_t b, int scale_d) {
  asm volatile("{\n.reg .pred p;\n.reg .b32 la, lb, hi;\n.reg .b64 da, db;\nsetp.ne.b32 p, %66, 0;\nmov.b32 hi, 0x40000040;\n"
    "add.u32 la, %64, 0;\nadd.u32 lb, %65, 0;\nmov.b64 da, {la, hi};\nmov.b64 db, {lb, hi};\n"
    "wgmma.mma_async.sync.aligned.m64n128k16.f32.bf16.bf16 "
    "{%0, %1, %2, %3, %4, %5, %6, %7, %8, %9, %10, %11, %12, %13, %14, %15, %16, %17, %18, %19, %20, %21, %22, %23, %24, %25, %26, %27, %28, %29, %30, %31, %32, %33, %34, %35, %36, %37, %38, %39, %40, %41, %42, %43, %44, %45, %46, %47, %48, %49, %50, %51, %52, %53, %54, %55, %56, %57, %58, %59, %60, %61, %62, %63}, "
    "da, db, p, 1, 1, 0, 1;\n"
    "add.u32 la, %64, 2;\nadd.u32 lb, %65, 128;\nmov.b64 da, {la, hi};\nmov.b64 db, {lb, hi};\n"
    "wgmma.mma_async.sync.aligned.m64n128k16.f32.bf16.bf16 "
    "{%0, %1, %2, %3, %4, %5, %6, %7, %8, %9, %10, %11, %12, %13, %14, %15, %16, %17, %18, %19, %20, %21, %22, %23, %24, %25, %26, %27, %28, %29, %30, %31, %32, %33, %34, %35, %36, %37, %38, %39, %40, %41, %42, %43, %44, %45, %46, %47, %48, %49, %50, %51, %52, %53, %54, %55, %56, %57, %58, %59, %60, %61, %62, %63}, "
    "da, db, 1, 1, 1, 0, 1;\n"
    "add.u32 la, %64, 4;\nadd.u32 lb, %65, 256;\nmov.b64 da, {la, hi};\nmov.b64 db, {lb, hi};\n"
    "wgmma.mma_async.sync.aligned.m64n128k16.f32.bf16.bf16 "
    "{%0, %1, %2, %3, %4, %5, %6, %7, %8, %9, %10, %11, %12, %13, %14, %15, %16, %17, %18, %19, %20, %21, %22, %23, %24, %25, %26, %27, %28, %29, %30, %31, %32, %33, %34, %35, %36, %37, %38, %39, %40, %41, %42, %43, %44, %45, %46, %47, %48, %49, %50, %51, %52, %53, %54, %55, %56, %57, %58, %59, %60, %61, %62, %63}, "
    "da, db, 1, 1, 1, 0, 1;\n"
    "add.u32 la, %64, 6;\nadd.u32 lb, %65, 384;\nmov.b64 da, {la, hi};\nmov.b64 db, {lb, hi};\n"
    "wgmma.mma_async.sync.aligned.m64n128k16.f32.bf16.bf16 "
    "{%0, %1, %2, %3, %4, %5, %6, %7, %8, %9, %10, %11, %12, %13, %14, %15, %16, %17, %18, %19, %20, %21, %22, %23, %24, %25, %26, %27, %28, %29, %30, %31, %32, %33, %34, %35, %36, %37, %38, %39, %40, %41, %42, %43, %44, %45, %46, %47, %48, %49, %50, %51, %52, %53, %54, %55, %56, %57, %58, %59, %60, %61, %62, %63}, "
    "da, db, 1, 1, 1, 0, 1;\n"
    "}\n"
    : "+f"(d[0]), "+f"(d[1]), "+f"(d[2]), "+f"(d[3]), "+f"(d[4]), "+f"(d[5]), "+f"(d[6]), "+f"(d[7]), "+f"(d[8]), "+f"(d[9]), "+f"(d[10]), "+f"(d[11]), "+f"(d[12]), "+f"(d[13]), "+f"(d[14]), "+f"(d[15]), "+f"(d[16]), "+f"(d[17]), "+f"(d[18]), "+f"(d[19]), "+f"(d[20]), "+f"(d[21]), "+f"(d[22]), "+f"(d[23]), "+f"(d[24]), "+f"(d[25]), "+f"(d[26]), "+f"(d[27]), "+f"(d[28]), "+f"(d[29]), "+f"(d[30]), "+f"(d[31]), "+f"(d[32]), "+f"(d[33]), "+f"(d[34]), "+f"(d[35]), "+f"(d[36]), "+f"(d[37]), "+f"(d[38]), "+f"(d[39]), "+f"(d[40]), "+f"(d[41]), "+f"(d[42]), "+f"(d[43]), "+f"(d[44]), "+f"(d[45]), "+f"(d[46]), "+f"(d[47]), "+f"(d[48]), "+f"(d[49]), "+f"(d[50]), "+f"(d[51]), "+f"(d[52]), "+f"(d[53]), "+f"(d[54]), "+f"(d[55]), "+f"(d[56]), "+f"(d[57]), "+f"(d[58]), "+f"(d[59]), "+f"(d[60]), "+f"(d[61]), "+f"(d[62]), "+f"(d[63])
    : "r"(a), "r"(b), "r"(scale_d));
}
__device__ __forceinline__ void wgmma4_n96_tb1(float (&d)[48], uint32_t a, uint32_t b, int scale_d) {
  asm volatile("{\n.reg .pred p;\n.reg .b32 la, lb, hi;\n.reg .b64 da, db;\nsetp.ne.b32 p, %50, 0;\nmov.b32 hi, 0x40000040;\n"
    "add.u32 la, %48, 0;\nadd.u32 lb, %49, 0;\nmov.b64 da, {la, hi};\nmov.b64 db, {lb, hi};\n"
    "wgmma.mma_async.sync.aligned.m64n96k16.f32.bf16.bf16 "
    "{%0, %1, %2, %3, %4, %5, %6, %7, %8, %9, %10, %11, %12, %13, %14, %15, %16, %17, %18, %19, %20, %21, %22, %23, %24, %25, %26, %27, %28, %29, %30, %31, %32, %33, %34, %35, %36, %37, %38, %39, %40, %41, %42, %43, %44, %45, %46, %47}, "
    "da, db, p, 1, 1, 0, 1;\n"
    "add.u32 la, %48, 2;\nadd.u32 lb, %49, 128;\nmov.b64 da, {la, hi};\nmov.b64 db, {lb, hi};\n"
    "wgmma.mma_async.sync.aligned.m64n96k16.f32.bf16.bf16 "
    "{%0, %1, %2, %3, %4, %5, %6, %7, %8, %9, %10, %11, %12, %13, %14, %15, %16, %17, %18, %19, %20, %21, %22, %23, %24, %25, %26, %27, %28, %29, %30, %31, %32, %33, %34, %35, %36, %37, %38, %39, %40, %41, %42, %43, %44, %45, %46, %47}, "
    "da, db, 1, 1, 1, 0, 1;\n"
    "add.u32 la, %48, 4;\nadd.u32 lb, %49, 256;\nmov.b64 da, {la, hi};\nmov.b64 db, {lb, hi};\n"
    "wgmma.mma_async.sync.aligned.m64n96k16.f32.bf16.bf16 "
    "{%0, %1, %2, %3, %4, %5, %6, %7, %8, %9, %10, %11, %12, %13, %14, %15, %16, %17, %18, %19, %20, %21, %22, %23, %24, %25, %26, %27, %28, %29, %30, %31, %32, %33, %34, %35, %36, %37, %38, %39, %40, %41, %42, %43, %44, %45, %46, %47}, "
    "da, db, 1, 1, 1, 0, 1;\n"
    "add.u32 la, %48, 6;\nadd.u32 lb, %49, 384;\nmov.b64 da, {la, hi};\nmov.b64 db, {lb, hi};\n"
    "wgmma.mma_async.sync.aligned.m64n96k16.f32.bf16.bf16 "
    "{%0, %1, %2, %3, %4, %5, %6, %7, %8, %9, %10, %11, %12, %13, %14, %15, %16, %17, %18, %19, %20, %21, %22, %23, %24, %25, %26, %27, %28, %29, %30, %31, %32, %33, %34, %35, %36, %37, %38, %39, %40, %41, %42, %43, %44, %45, %46, %47}, "
    "da, db, 1, 1, 1, 0, 1;\n"
    "}\n"
    : "+f"(d[0]), "+f"(d[1]), "+f"(d[2]), "+f"(d[3]), "+f"(d[4]), "+f"(d[5]), "+f"(d[6]), "+f"(d[7]), "+f"(d[8]), "+f"(d[9]), "+f"(d[10]), "+f"(d[11]), "+f"(d[12]), "+f"(d[13]), "+f"(d[14]), "+f"(d[15]), "+f"(d[16]), "+f"(d[17]), "+f"(d[18]), "+f"(d[19]), "+f"(d[20]), "+f"(d[21]), "+f"(d[22]), "+f"(d[23]), "+f"(d[24]), "+f"(d[25]), "+f"(d[26]), "+f"(d[27]), "+f"(d[28]), "+f"(d[29]), "+f"(d[30]), "+f"(d[31]), "+f"(d[32]), "+f"(d[33]), "+f"(d[34]), "+f"(d[35]), "+f"(d[36]), "+f"(d[37]), "+f"(d[38]), "+f"(d[39]), "+f"(d[40]), "+f"(d[41]), "+f"(d[42]), "+f"(d[43]), "+f"(d[44]), "+f"(d[45]), "+f"(d[46]), "+f"(d[47])
    : "r"(a), "r"(b), "r"(scale_d));
}

__device__ __forceinline__ void bar_arrive(int id, int n) { asm volatile("bar.arrive %0, %1;" :: "r"(id), "r"(n) : "memory"); }
__device__ __forceinline__ void bar_sync(int id, int n) { asm volatile("bar.sync %0, %1;" :: "r"(id), "r"(n) : "memory"); }
__device__ __forceinline__ unsigned ld_rlx(const unsigned* p) { unsigned v; asm volatile("ld.relaxed.gpu.global.u32 %0, [%1];" : "=r"(v) : "l"(p) : "memory"); return v; }
__device__ __forceinline__ void red_add(unsigned* p) { asm volatile("red.relaxed.gpu.global.add.u32 [%0], 1;" :: "l"(p) : "memory"); }
__device__ __forceinline__ void wait_cnt(const unsigned* p, unsigned target) {
  uint32_t n = 0;
  while ((int)(ld_rlx(p) - target) < 0) { if (++n > (1u << 20)) __trap(); }
}
__device__ __forceinline__ float bf_lo(uint32_t v) { return __uint_as_float(v << 16); }
__device__ __forceinline__ float bf_hi(uint32_t v) { return __uint_as_float(v & 0xffff0000u); }
__device__ __forceinline__ uint32_t pack2(float lo, float hi) { uint32_t r; asm("cvt.rn.bf16x2.f32 %0, %1, %2;" : "=r"(r) : "f"(hi), "f"(lo)); return r; }
__device__ __forceinline__ float bfr(float v) { return __bfloat162float(__float2bfloat16_rn(v)); }
__device__ __forceinline__ float gelu_f(float t) {
  const float k0 = 0.7978845608028654f, k1 = k0 * 0.044715f;
  float th; asm("tanh.approx.f32 %0, %1;" : "=f"(th) : "f"(t * fmaf(t * t, k1, k0)));
  const float hf = 0.5f * t;
  return fmaf(hf, th, hf);
}
__device__ __forceinline__ float silu_f(float z) {
  const float hz = 0.5f * z;
  float th; asm("tanh.approx.f32 %0, %1;" : "=f"(th) : "f"(hz));
  return fmaf(hz, th, hz);
}
__device__ __forceinline__ uint32_t tagf(float v, uint32_t tag) { return (__float_as_uint(v) & ~3u) | tag; }
__device__ __forceinline__ uint4 ld_msg(const void* p) { uint4 v; asm volatile("ld.relaxed.gpu.global.v4.u32 {%0,%1,%2,%3}, [%4];" : "=r"(v.x), "=r"(v.y), "=r"(v.z), "=r"(v.w) : "l"(p) : "memory"); return v; }
__device__ __forceinline__ void st_msg(void* p, uint32_t a, uint32_t b, uint32_t c, uint32_t d) { asm volatile("st.relaxed.gpu.global.v4.u32 [%0], {%1,%2,%3,%4};" :: "l"(p), "r"(a), "r"(b), "r"(c), "r"(d) : "memory"); }
__device__ __forceinline__ uint32_t stale(const uint4& v, uint32_t tag) { return ((v.x ^ tag) | (v.y ^ tag) | (v.z ^ tag) | (v.w ^ tag)) & 3u; }
__device__ __forceinline__ void sts4(uint32_t a, uint32_t x, uint32_t y, uint32_t z, uint32_t w) { asm volatile("st.shared.v4.u32 [%0], {%1,%2,%3,%4};" :: "r"(a), "r"(x), "r"(y), "r"(z), "r"(w) : "memory"); }
__device__ __forceinline__ void tma_st2d(const CUtensorMap* m, uint32_t src, int c0, int c1) {
  asm volatile("cp.async.bulk.tensor.2d.global.shared::cta.bulk_group [%0, {%2, %3}], [%1];" :: "l"(m), "r"(src), "r"(c0), "r"(c1) : "memory");
}
__device__ __forceinline__ void fence_async_smem() { asm volatile("fence.proxy.async.shared::cta;" ::: "memory"); }
__device__ __forceinline__ uint4 ldg_nc(const void* p) { uint4 v; asm volatile("ld.global.nc.v4.u32 {%0,%1,%2,%3}, [%4];" : "=r"(v.x), "=r"(v.y), "=r"(v.z), "=r"(v.w) : "l"(p)); return v; }
__device__ __forceinline__ void stg4(void* p, uint32_t a, uint32_t b, uint32_t c, uint32_t d) { asm volatile("st.global.v4.u32 [%0], {%1,%2,%3,%4};" :: "l"(p), "r"(a), "r"(b), "r"(c), "r"(d) : "memory"); }
__device__ __forceinline__ float4 lds4f(uint32_t a) { float4 v; asm volatile("ld.shared.v4.f32 {%0,%1,%2,%3}, [%4];" : "=f"(v.x), "=f"(v.y), "=f"(v.z), "=f"(v.w) : "r"(a)); return v; }
__device__ __forceinline__ uint4 lds4u(uint32_t a) { uint4 v; asm volatile("ld.shared.v4.u32 {%0,%1,%2,%3}, [%4];" : "=r"(v.x), "=r"(v.y), "=r"(v.z), "=r"(v.w) : "r"(a) : "memory"); return v; }
__device__ __forceinline__ float2 lds2f(uint32_t a) { float2 v; asm volatile("ld.shared.v2.f32 {%0,%1}, [%2];" : "=f"(v.x), "=f"(v.y) : "r"(a)); return v; }
__device__ __forceinline__ void st_async4(uint32_t raddr, uint32_t a, uint32_t b, uint32_t c, uint32_t d, uint32_t rbar) {
  asm volatile("st.async.weak.shared::cluster.mbarrier::complete_tx::bytes.v4.b32 [%0], {%1,%2,%3,%4}, [%5];"
    :: "r"(raddr), "r"(a), "r"(b), "r"(c), "r"(d), "r"(rbar) : "memory");
}
__device__ __forceinline__ float wsum(float v) {
#pragma unroll
  for (int o = 16; o > 0; o >>= 1) v += __shfl_xor_sync(0xffffffffu, v, o);
  return v;
}
__device__ __forceinline__ float sum8(const uint4& v) {
  return ((bf_lo(v.x) + bf_hi(v.x)) + (bf_lo(v.y) + bf_hi(v.y))) + ((bf_lo(v.z) + bf_hi(v.z)) + (bf_lo(v.w) + bf_hi(v.w)));
}

struct Ctx {
  uint32_t sm;
  uint32_t da;
  uint32_t db;
  int lane;
};

template <int N, int TB>
__device__ __forceinline__ void mma_step(float (&acc)[N / 2], const Ctx& c, int st, uint32_t ph, int accum) {
  mbar_wait(c.sm + OFF_BAR + BAR_FULL + 8 * st, ph);
  const uint32_t a = c.da + st * (STB >> 4), b = c.db + st * (STB >> 4) + (TB ? (512u << 16) : (1u << 16));
  wg_fence();
  if constexpr (N == 128 && TB == 0) wgmma4_n128_tb0(acc, a, b, accum);
  if constexpr (N == 128 && TB == 1) wgmma4_n128_tb1(acc, a, b, accum);
  if constexpr (N == 96) wgmma4_n96_tb1(acc, a, b, accum);
  wg_commit();
}
template <int N, int TB, int S>
__device__ __forceinline__ void mma_step1(float (&acc)[N / 2], const Ctx& c) {
  if (S < 8) mbar_wait(c.sm + OFF_BAR + BAR_XF + 8 * S, 0);
  mbar_wait(c.sm + OFF_BAR + BAR_BF + 8 * (S & 3), (S >> 2) & 1);
  const uint32_t a = c.da + (xslot(S & 7) >> 4), b = c.db + ((bslot(S & 3) - 16384) >> 4) + (TB ? (512u << 16) : (1u << 16));
  wg_fence();
  if constexpr (N == 128 && TB == 0) wgmma4_n128_tb0(acc, a, b, (S & 7) != 0);
  if constexpr (N == 128 && TB == 1) wgmma4_n128_tb1(acc, a, b, (S & 7) != 0);
  if constexpr (N == 96) wgmma4_n96_tb1(acc, a, b, (S & 7) != 0);
  wg_commit();
}
template <int S>
__device__ __forceinline__ void release1(const Ctx& c) {
  if (c.lane == 0) {
    if (S < 20) mbar_arrive(c.sm + OFF_BAR + BAR_BE + 8 * (S & 3));
    if (S == 17) mbar_arrive(c.sm + OFF_BAR + BAR_EMPTY);
    if constexpr (S >= 19) mbar_arrive(c.sm + OFF_BAR + BAR_EMPTY + 8 * (S - 18));
  }
}
template <int V> struct IC { static constexpr int value = V; };
template <int S0, int S1, class F>
__device__ __forceinline__ void static_for(F&& f) {
  if constexpr (S0 < S1) { f(IC<S0>{}); static_for<S0 + 1, S1>(f); }
}
__device__ __forceinline__ void release(const Ctx& c, int st) {
  if (c.lane == 0) mbar_arrive(c.sm + OFF_BAR + BAR_EMPTY + 8 * st);
}

template <int G>
__device__ __forceinline__ void epi_ab(const float (&acc)[64], const Ctx& c, float a0, float b0, float a1, float b1, uint32_t stg) {
  uint32_t w0[4], w1[4];
#pragma unroll
  for (int i = 0; i < 4; i++) {
    float2 cs = lds2f(c.sm + OFF_VAB + (32 * G + 8 * i) * 4 + (c.lane & 3) * 8);
    const int r = 4 * (4 * G + i);
    w0[i] = pack2(fmaf(a0, acc[r], b0 * cs.x), fmaf(a0, acc[r + 1], b0 * cs.y));
    w1[i] = pack2(fmaf(a1, acc[r + 2], b1 * cs.x), fmaf(a1, acc[r + 3], b1 * cs.y));
  }
  sts4(stg + G * 8192, w0[0], w0[1], w0[2], w0[3]);
  sts4(stg + G * 8192 + 512, w1[0], w1[1], w1[2], w1[3]);
}
template <int G, int VG, int NA>
__device__ __forceinline__ void epi_h(const float (&acc)[NA], const Ctx& c, float a0, float b0, float a1, float b1, uint32_t stg) {
  uint32_t w0[4], w1[4];
#pragma unroll
  for (int i = 0; i < 4; i++) {
    float4 v = lds4f(c.sm + OFF_VH + (16 * VG + 4 * i) * 16 + (c.lane & 3) * 16);
    const int r = 4 * (4 * G + i);
    w0[i] = pack2(gelu_f(fmaf(a0, acc[r], fmaf(b0, v.x, v.z))), gelu_f(fmaf(a0, acc[r + 1], fmaf(b0, v.y, v.w))));
    w1[i] = pack2(gelu_f(fmaf(a1, acc[r + 2], fmaf(b1, v.x, v.z))), gelu_f(fmaf(a1, acc[r + 3], fmaf(b1, v.y, v.w))));
  }
  sts4(stg + G * 8192, w0[0], w0[1], w0[2], w0[3]);
  sts4(stg + G * 8192 + 512, w1[0], w1[1], w1[2], w1[3]);
}
template <int G>
__device__ __forceinline__ void epi_g(const float (&acc)[64], const Ctx& c, uint32_t stg, uint4& o0, uint4& o1) {
  uint32_t w0[4], w1[4];
#pragma unroll
  for (int i = 0; i < 4; i++) {
    uint32_t bw; asm volatile("ld.shared.u32 %0, [%1];" : "=r"(bw) : "r"(c.sm + OFF_B2 + (32 * G + 8 * i) * 2 + (c.lane & 3) * 4));
    const float2 b = make_float2(bf_lo(bw), bf_hi(bw));
    const int r = 4 * (4 * G + i);
    w0[i] = pack2(silu_f(acc[r] + b.x), silu_f(acc[r + 1] + b.y));
    w1[i] = pack2(silu_f(acc[r + 2] + b.x), silu_f(acc[r + 3] + b.y));
  }
  const int r8 = c.lane & 7, mi = c.lane >> 3;
  const uint32_t wa = stg + r8 * 128 + ((((G & 1) * 4 + mi) ^ r8) << 4);
  __syncwarp();
  asm volatile("stmatrix.sync.aligned.m8n8.x4.shared.b16 [%0], {%1,%2,%3,%4};" :: "r"(wa), "r"(w0[0]), "r"(w0[1]), "r"(w0[2]), "r"(w0[3]) : "memory");
  asm volatile("stmatrix.sync.aligned.m8n8.x4.shared.b16 [%0], {%1,%2,%3,%4};" :: "r"(wa + 1024), "r"(w1[0]), "r"(w1[1]), "r"(w1[2]), "r"(w1[3]) : "memory");
  __syncwarp();
  const int rr = c.lane >> 2;
  const uint32_t ra = stg + rr * 128 + ((((G & 1) * 4 + (c.lane & 3)) ^ rr) << 4);
  o0 = lds4u(ra);
  o1 = lds4u(ra + 1024);
}

template <int ROLE>
__device__ __forceinline__ void tail(float (&y)[64], float (&m)[64], const Ctx& c, const Params& p, int tid, size_t ooff) {
  const uint32_t peer = ROLE ^ 1;
  uint4 g[4], xr[4];
  const uint32_t stg = c.sm + OFF_G + (tid >> 5) * 2048;
  const uint32_t rg = mapa(c.sm + OFF_G + tid * 16, peer), rgb = mapa(c.sm + OFF_BAR + BAR_G, peer);
  constexpr int S0 = NSTEPS - NYB;
#pragma unroll
  for (int s = S0; s < NSTEPS; s++) {
    mma_step<128, 1>(y, c, s % NST, (s / NST) & 1, 1);
    if (s == S0) {
      xr[0] = ldg_nc(p.x + ooff); xr[1] = ldg_nc(p.x + ooff + 8 * DM);
      xr[2] = ldg_nc(p.x + ooff + 32); xr[3] = ldg_nc(p.x + ooff + 8 * DM + 32);
    }
    wg_wait<1>();
    if (s == S0) {
      if (s - 1 < NSTEPS - NST) release(c, (s - 1) % NST);
      asm volatile("barrier.cluster.wait.aligned;" ::: "memory");
      if (ROLE == 1) reg_fence(m);
    }
    if (s == S0 + 1 && c.lane == 0) mbar_arrive_cluster(mapa(c.sm + OFF_BAR + BAR_OK, peer));
    if (ROLE == 1) {
      if (s == S0) {
        uint4 t0, t1;
        epi_g<0>(m, c, stg, t0, t1); st_async4(rg, t0.x, t0.y, t0.z, t0.w, rgb); st_async4(rg + 4096, t1.x, t1.y, t1.z, t1.w, rgb);
        epi_g<1>(m, c, stg, t0, t1); st_async4(rg + 8192, t0.x, t0.y, t0.z, t0.w, rgb); st_async4(rg + 12288, t1.x, t1.y, t1.z, t1.w, rgb);
      }
      if (s == S0 + 1) epi_g<2>(m, c, stg, g[0], g[1]);
      if (s == S0 + 2) epi_g<3>(m, c, stg, g[2], g[3]);
    }
  }
  if (ROLE == 0) {
    mbar_wait(c.sm + OFF_BAR + BAR_G, 0);
#pragma unroll
    for (int v = 0; v < 4; v++) g[v] = lds4u(c.sm + OFF_G + v * 4096 + tid * 16);
  }
  mbar_wait(c.sm + OFF_BAR + BAR_OK, 0);
  const uint32_t rl = mapa(c.sm + LAND_STAGE * STB + tid * 16, peer), rlb = mapa(c.sm + OFF_BAR + BAR_Y, peer);
  wg_wait<0>();
  reg_fence(y);
  TLC(8);
  constexpr int SND = ROLE == 0 ? 32 : 0, KEEP = 32 - SND;
#pragma unroll
  for (int v = 0; v < 8; v++)
    st_async4(rl + v * 4096, __float_as_uint(y[SND + 4 * v]), __float_as_uint(y[SND + 4 * v + 1]), __float_as_uint(y[SND + 4 * v + 2]), __float_as_uint(y[SND + 4 * v + 3]), rlb);
  mbar_wait(c.sm + OFF_BAR + BAR_Y, 0);
  TLC(9);
#pragma unroll
  for (int G = 0; G < 2; G++) {
    float4 r[4];
#pragma unroll
    for (int i = 0; i < 4; i++) {
      uint4 t = lds4u(c.sm + LAND_STAGE * STB + (4 * G + i) * 4096 + tid * 16);
      r[i] = make_float4(__uint_as_float(t.x), __uint_as_float(t.y), __uint_as_float(t.z), __uint_as_float(t.w));
    }
    uint32_t o0[4], o1[4];
    const uint32_t g0[4] = {g[2 * G].x, g[2 * G].y, g[2 * G].z, g[2 * G].w}, g1[4] = {g[2 * G + 1].x, g[2 * G + 1].y, g[2 * G + 1].z, g[2 * G + 1].w};
    const uint32_t x0[4] = {xr[2 * G].x, xr[2 * G].y, xr[2 * G].z, xr[2 * G].w}, x1[4] = {xr[2 * G + 1].x, xr[2 * G + 1].y, xr[2 * G + 1].z, xr[2 * G + 1].w};
#pragma unroll
    for (int i = 0; i < 4; i++) {
      const int a = KEEP + 4 * (4 * G + i);
      o0[i] = pack2(fmaf(y[a] + r[i].x, bf_lo(g0[i]), bf_lo(x0[i])), fmaf(y[a + 1] + r[i].y, bf_hi(g0[i]), bf_hi(x0[i])));
      o1[i] = pack2(fmaf(y[a + 2] + r[i].z, bf_lo(g1[i]), bf_lo(x1[i])), fmaf(y[a + 3] + r[i].w, bf_hi(g1[i]), bf_hi(x1[i])));
    }
    stg4(p.out + ooff + 32 * G, o0[0], o0[1], o0[2], o0[3]);
    stg4(p.out + ooff + 32 * G + 8 * DM, o1[0], o1[1], o1[2], o1[3]);
  }
  TLC(10);
}

__global__ void __cluster_dims__(2, 1, 1) __launch_bounds__(384, 1) fused_kernel(const __grid_constant__ Params p) {
  extern __shared__ __align__(1024) uint8_t smem_raw[];
  const uint32_t sm = (uint32_t)__cvta_generic_to_shared(smem_raw);
  const int tid = threadIdx.x, lane = tid & 31;
  const int warp = __shfl_sync(0xffffffffu, tid >> 5, 0);
  int lc;
  {
    const int c = blockIdx.x >> 1;
    if (c < 4) lc = 4 + c;
    else if (c < 36) lc = ((c - 4) & 7) * 8 + ((c - 4) >> 3);
    else lc = (1 + (c - 36) % 7) * 8 + 4 + (c - 36) / 7;
  }
  const int role = blockIdx.x & 1, cb = lc & 3, rb = lc >> 2, j = cb * 2 + role, lb = lc * 2 + role;
  const uint32_t bars = sm + OFF_BAR;
  TLC(0);
#define EPOCH() mbar_wait(bars + BAR_E, 0); unsigned epoch; asm volatile("ld.shared.u32 %0, [%1];" : "=r"(epoch) : "r"(bars + OFF_EPOCH) : "memory"); const uint32_t tag = epoch & 3
  if (warp >= 8) {
    asm volatile("setmaxnreg.dec.sync.aligned.u32 120;");
    if (warp == 8) {
      {
        if (elect_one()) {
          for (int s = 0; s < 8; s++) mbar_init(bars + BAR_XF + 8 * s, 1);
          for (int s = 0; s < 4; s++) { mbar_init(bars + BAR_BF + 8 * s, 1); mbar_init(bars + BAR_BE + 8 * s, 8); }
          fence_async_smem();
          const CUtensorMap* md = j < 4 ? &p.mdre : &p.mdim;
          for (int k = 0; k < INIT_X; k++) {
            mbar_expect_tx(bars + BAR_XF + 8 * k, 16384);
            tma2d(sm + xslot(k), &p.mx, k * 64, rb * 128, bars + BAR_XF + 8 * k);
            if (k < 4) {
              mbar_expect_tx(bars + BAR_BF + 8 * k, 16384);
              tma2d(sm + bslot(k), md, k * 64, (j & 3) * 128, bars + BAR_BF + 8 * k);
            }
          }
          for (int s = 0; s < NST; s++) { mbar_init(bars + BAR_FULL + 8 * s, 1); mbar_init(bars + BAR_EMPTY + 8 * s, 8); }
          mbar_init(bars + BAR_V1, 1); mbar_init(bars + BAR_V2, 2); mbar_init(bars + BAR_FREE, 1); mbar_init(bars + BAR_E, 1);
          mbar_init(bars + BAR_G, 1); mbar_init(bars + BAR_Y, 1); mbar_init(bars + BAR_OK, 8);
          asm volatile("fence.mbarrier_init.release.cluster;" ::: "memory");
          fence_async_smem();
          mbar_expect_tx(bars + BAR_G, 16384);
          mbar_expect_tx(bars + BAR_Y, 32768);
        }
        __syncwarp();
      }
      __syncthreads();
      asm volatile("barrier.cluster.arrive.relaxed.aligned;" ::: "memory");
      if (elect_one()) {
        asm volatile("prefetch.tensormap [%0];" :: "l"(&p.mw1) : "memory");
        asm volatile("prefetch.tensormap [%0];" :: "l"(&p.mcr) : "memory");
        asm volatile("prefetch.tensormap [%0];" :: "l"(&p.mci) : "memory");
        asm volatile("prefetch.tensormap [%0];" :: "l"(&p.mab) : "memory");
        if (role) {
          asm volatile("prefetch.tensormap [%0];" :: "l"(&p.mh) : "memory");
          asm volatile("prefetch.tensormap [%0];" :: "l"(&p.mw2) : "memory");
        }
        int st = 0; uint32_t ph = 0;
        const int y0 = role ? 46 : 0;
        const int row0 = rb * 128;
#define P_ACQ() mbar_wait(bars + BAR_EMPTY + 8 * st, ph); const uint32_t fb = bars + BAR_FULL + 8 * st, sa = sm + st * STB, sb = sa + 16384; mbar_expect_tx(fb, STB)
#define P_ADV() if (++st == NST) { st = 0; ph ^= 1; }
        const CUtensorMap* md = j < 4 ? &p.mdre : &p.mdim;
        for (int k = INIT_X; k < 8; k++) {
          mbar_wait(bars + BAR_XF + 8 * (k - INIT_X), 0);
          mbar_expect_tx(bars + BAR_XF + 8 * k, 16384);
          tma2d(sm + xslot(k), &p.mx, k * 64, row0, bars + BAR_XF + 8 * k);
          if (k < 4) {
            mbar_expect_tx(bars + BAR_BF + 8 * k, 16384);
            tma2d(sm + bslot(k), md, k * 64, (j & 3) * 128, bars + BAR_BF + 8 * k);
          }
        }
        for (int k = 4; k < 24; k++) {
          const uint32_t fb = bars + BAR_BF + 8 * (k & 3), sb = sm + bslot(k & 3);
          mbar_wait(bars + BAR_BE + 8 * (k & 3), ((k >> 2) & 1) ^ 1);
          mbar_expect_tx(fb, 16384);
          if (k < 8) tma2d(sb, md, k * 64, (j & 3) * 128, fb);
          else tma3d(sb, &p.mw1, j * 224 + (k >> 4) * 96, (k & 7) * 64, 0, fb);
        }
        TLREC(11);
        EPOCH();
        if (!role) wait_cnt(&g_cnt[C_AB + cb * 32], 16 * epoch);
        wait_cnt(&g_cnt[C_AB + (4 + cb) * 32], 16 * epoch);
        asm volatile("fence.proxy.async.global;" ::: "memory");
        TLREC(12);
        const int nya = role ? 18 - NYB : 46;
        for (int k = y0; k < y0 + nya; k++) {
          P_ACQ(); tma2d(sa, k < 32 ? &p.mcr : &p.mci, (k & 31) * 64, row0, fb); tma3d(sb, &p.mab, 0, k * 64, cb * 2, fb); P_ADV();
        }
        if (role) {
          TLREC(13);
          wait_cnt(&g_cnt[C_H + rb * 32], 16 * epoch);
          asm volatile("fence.proxy.async.global;" ::: "memory");
          TLREC(14);
          for (int k = 0; k < 28; k++) {
            P_ACQ(); tma2d(sa, &p.mh, k * 64, row0, fb); tma5d(sb, &p.mw2, cb * 128, 2 * k, fb); tma5d(sb + 8192, &p.mw2, cb * 128 + 64, 2 * k, fb); P_ADV();
          }
          for (int k = 64 - NYB; k < 64; k++) {
            P_ACQ(); tma2d(sa, &p.mci, (k & 31) * 64, row0, fb); tma3d(sb, &p.mab, 0, k * 64, cb * 2, fb); P_ADV();
          }
        }
        red_add(&g_cnt[C_DONE]);
      }
    } else if (warp == 9) {
      unsigned done0 = 0;
      if (lane == 0) done0 = ld_rlx(&g_cnt[C_DONE]);
      const int d0 = lb * 8;
      const __nv_bfloat16* d = (d0 < DM ? p.dre + (size_t)d0 * DM : p.dim + (size_t)(d0 - DM) * DM) + lane * 8;
      __syncthreads();
      asm volatile("barrier.cluster.arrive.relaxed.aligned;" ::: "memory");
      mbar_wait(bars + BAR_XF + 8 * DLY_D, 0);
      uint4 u[8][2];
#pragma unroll
      for (int r = 0; r < 8; r++) { u[r][0] = ldg_nc(d + r * DM); u[r][1] = ldg_nc(d + r * DM + 256); }
      if (lane == 0) { asm volatile("st.shared.u32 [%0], %1;" :: "r"(bars + OFF_EPOCH), "r"((done0 >> 7) + 1) : "memory"); mbar_arrive(bars + BAR_E); TLREC(23); }
      __syncwarp();
      EPOCH();
      float t[8];
#pragma unroll
      for (int r = 0; r < 8; r++) t[r] = sum8(u[r][0]) + sum8(u[r][1]);
#pragma unroll
      for (int o = 4; o > 0; o >>= 1) {
#pragma unroll
        for (int r = 0; r < o; r++) {
          const bool up = lane & o;
          const float keep = up ? t[r + o] : t[r], give = up ? t[r] : t[r + o];
          t[r] = keep + __shfl_xor_sync(0xffffffffu, give, o);
        }
      }
      t[0] += __shfl_xor_sync(0xffffffffu, t[0], 8);
      t[0] += __shfl_xor_sync(0xffffffffu, t[0], 16);
      if (lane < 8) asm volatile("st.relaxed.gpu.global.u32 [%0], %1;" :: "l"(&g_cs[d0 + lane]), "r"(tagf(t[0], tag)) : "memory");
      if (lane == 0) TLREC(15);
      uint4 cv;
      { uint32_t n = 0; do { cv = ld_msg(&g_cs[j * 128 + lane * 4]); if (++n > (1u << 20)) __trap(); } while (__any_sync(0xffffffffu, stale(cv, tag))); }
      sts4(sm + OFF_VAB + lane * 16, cv.x, cv.y, cv.z, cv.w);
      __syncwarp();
      if (lane == 0) { mbar_arrive(bars + BAR_V1); TLREC(16); }
      if (lane == 0) { asm volatile("prefetch.tensormap [%0];" :: "l"(&p.sab) : "memory"); asm volatile("prefetch.tensormap [%0];" :: "l"(&p.sh) : "memory"); }
      for (int tile = 0; tile < 3; tile++) {
        bar_sync(1 + tile, 288);
        if (elect_one()) {
          TLREC(25 + tile);
          const CUtensorMap* m = tile ? &p.sh : &p.sab;
          const int c0 = tile == 0 ? (j & 3) * 128 : j * 224 + (tile - 1) * 96, r0 = (tile == 0 ? (j >> 2) * SEQ : 0) + rb * 128;
          for (int g = 0; g < (tile == 1 ? 3 : 4); g++) tma_st2d(m, sm + OFF_STG + g * 8192, c0 + g * 32, r0);
          asm volatile("cp.async.bulk.commit_group;\ncp.async.bulk.wait_group.read 0;" ::: "memory");
          mbar_arrive(bars + BAR_FREE);
          asm volatile("cp.async.bulk.wait_group 0;" ::: "memory");
          red_add(tile ? &g_cnt[C_H + rb * 32] : &g_cnt[C_AB + j * 32]);
          TLREC(17 + tile);
        }
        __syncwarp();
      }
    } else {
      const int cl = lane < 28 ? lane : 27;
      const __nv_bfloat16* w = p.w1 + (size_t)(rb * 32 + (warp - 10) * 16) * FF + j * 224 + cl * 8;
      __syncthreads();
      asm volatile("barrier.cluster.arrive.relaxed.aligned;" ::: "memory");
      uint4 v[16];
      {
        const int r = j * 16 + (warp - 10) * 8 + (lane >> 2);
        const uint32_t rowa = sm + r * 128, c0 = (((lane & 3) * 2) ^ (r & 7)) << 4;
        float piv = 0.f, sa = 0.f, sb = 0.f, qa = 0.f, qb = 0.f;
#pragma unroll 1
        for (int k = 0; k < 8; k++) {
          mbar_wait(bars + BAR_XF + 8 * k, 0);
          if (k == 0) { uint32_t t; asm volatile("ld.shared.u32 %0, [%1];" : "=r"(t) : "r"(rowa + ((r & 7) << 4)) : "memory"); piv = bf_lo(t); }
          const uint4 t0 = lds4u(rowa + xslot(k) + c0), t1 = lds4u(rowa + xslot(k) + (c0 ^ 16));
          const uint32_t ww[8] = {t0.x, t0.y, t0.z, t0.w, t1.x, t1.y, t1.z, t1.w};
#pragma unroll
          for (int i = 0; i < 8; i++) {
            const float a = bf_lo(ww[i]) - piv, b = bf_hi(ww[i]) - piv;
            sa += a; sb += b; qa = fmaf(a, a, qa); qb = fmaf(b, b, qb);
          }
        }
        float s1 = sa + sb, s2 = qa + qb;
        s1 += __shfl_xor_sync(0xffffffffu, s1, 1); s2 += __shfl_xor_sync(0xffffffffu, s2, 1);
        s1 += __shfl_xor_sync(0xffffffffu, s1, 2); s2 += __shfl_xor_sync(0xffffffffu, s2, 2);
        s1 *= 1.0f / DM;
        const float mean = piv + s1, var = fmaxf(fmaf(s2, 1.0f / DM, -s1 * s1), 0.f);
        const float m1 = bfr(mean), d1 = bfr(__fsqrt_rn(bfr(bfr(var) + 1e-5f))), i1 = __frcp_rn(d1);
        const float m2 = bfr((mean - m1) * i1), d2 = bfr(__fsqrt_rn(bfr(bfr(var * i1 * i1) + 1e-5f))), i2 = __frcp_rn(d2);
        EPOCH();
        if ((lane & 3) == 0) st_msg(&g_stats[rb * 128 + r], tagf(i1, tag), tagf(-m1 * i1, tag), tagf(i1 * i2, tag), tagf(-(m1 * i1 + m2) * i2, tag));
        if (warp == 10 && lane == 0) TLREC(20);
      }
#pragma unroll
      for (int i = 0; i < 16; i++) v[i] = ldg_nc(w + (size_t)i * FF);
      float s[8] = {0.f, 0.f, 0.f, 0.f, 0.f, 0.f, 0.f, 0.f};
#pragma unroll
      for (int r = 0; r < 16; r++) {
        s[0] += bf_lo(v[r].x); s[1] += bf_hi(v[r].x); s[2] += bf_lo(v[r].y); s[3] += bf_hi(v[r].y);
        s[4] += bf_lo(v[r].z); s[5] += bf_hi(v[r].z); s[6] += bf_lo(v[r].w); s[7] += bf_hi(v[r].w);
      }
      EPOCH();
      float4* s4 = reinterpret_cast<float4*>(smem_raw);
      if (warp == 11) {
        if (lane < 28) { s4[OFF_VH / 16 + lane * 2] = make_float4(s[0], s[1], s[2], s[3]); s4[OFF_VH / 16 + lane * 2 + 1] = make_float4(s[4], s[5], s[6], s[7]); }
        const uint2 b2v = *reinterpret_cast<const uint2*>(p.b2 + cb * 128 + lane * 4);
        reinterpret_cast<uint2*>(smem_raw + OFF_B2)[lane] = b2v;
      }
      bar_sync(4, 64);
      if (warp == 10 && lane < 28) {
        const float4 o0 = s4[OFF_VH / 16 + lane * 2], o1 = s4[OFF_VH / 16 + lane * 2 + 1];
        float* dst = &g_csw[rb * FF + j * 224 + lane * 8];
        st_msg(dst, tagf(s[0] + o0.x, tag), tagf(s[1] + o0.y, tag), tagf(s[2] + o0.z, tag), tagf(s[3] + o0.w, tag));
        st_msg(dst + 4, tagf(s[4] + o1.x, tag), tagf(s[5] + o1.y, tag), tagf(s[6] + o1.z, tag), tagf(s[7] + o1.w, tag));
      }
      bar_sync(4, 64);
      const int q = (warp - 10) * 28 + cl;
      const uint2 bb = *reinterpret_cast<const uint2*>(p.b1 + j * 224 + q * 4);
      float4 acc;
      uint32_t n = 0, bad;
      do {
        uint4 m[16];
#pragma unroll
        for (int r = 0; r < 16; r++) m[r] = ld_msg(&g_csw[r * FF + j * 224 + q * 4]);
        acc = make_float4(0.f, 0.f, 0.f, 0.f); bad = 0;
#pragma unroll
        for (int r = 0; r < 16; r++) {
          bad |= stale(m[r], tag);
          acc.x += __uint_as_float(m[r].x); acc.y += __uint_as_float(m[r].y); acc.z += __uint_as_float(m[r].z); acc.w += __uint_as_float(m[r].w);
        }
        if (++n > (1u << 20)) __trap();
      } while (__any_sync(0xffffffffu, bad));
      if (lane < 28) {
        s4[OFF_VH / 16 + q * 2] = make_float4(acc.x, acc.y, bf_lo(bb.x), bf_hi(bb.x));
        s4[OFF_VH / 16 + q * 2 + 1] = make_float4(acc.z, acc.w, bf_lo(bb.y), bf_hi(bb.y));
      }
      __syncwarp();
      if (lane == 0) { mbar_arrive(bars + BAR_V2); if (warp == 10) TLREC(24); }
    }
  } else {
    asm volatile("setmaxnreg.inc.sync.aligned.u32 192;");
    __syncthreads();
    asm volatile("barrier.cluster.arrive.relaxed.aligned;" ::: "memory");
    Ctx c; c.sm = sm; c.lane = lane;
    c.da = (((sm + (warp >> 2) * 8192) & 0x3FFFF) >> 4) | (1u << 16); c.db = ((sm + 16384) & 0x3FFFF) >> 4;
    const int rl = warp * 16 + (lane >> 2);
    const int q8 = (lane & 3) * 8;
    const uint32_t stg = sm + OFF_STG + rl * 64 + (lane & 3) * 16;
    float P[64], Q[48], R[64], Y[64], M[64];
    static_for<0, 8>([&](auto S_) {
      constexpr int S = decltype(S_)::value;
      mma_step1<128, 0, S>(P, c);
      if (S == 0) TLC(1);
      if constexpr (S > 0) { wg_wait<1>(); release1<S - 1>(c); }
    });
    TLC(2);
    EPOCH();
    uint4 m0, m1;
    float4 s0, s1;
    static_for<8, 16>([&](auto S_) {
      constexpr int S = decltype(S_)::value;
      mma_step1<96, 1, S>(Q, c);
      if (S == 8) { m0 = ld_msg(&g_stats[rb * 128 + rl]); m1 = ld_msg(&g_stats[rb * 128 + rl + 8]); }
      wg_wait<1>();
      release1<S - 1>(c);
      if (S == AB0) {
        reg_fence(P);
        uint32_t n = 0;
        while (stale(m0, tag) | stale(m1, tag)) { m0 = ld_msg(&g_stats[rb * 128 + rl]); m1 = ld_msg(&g_stats[rb * 128 + rl + 8]); if (++n > (1u << 20)) __trap(); }
        const float sg = j < 4 ? 1.f : -1.f;
        s0 = make_float4(__uint_as_float(m0.x) * sg, __uint_as_float(m0.y) * sg, __uint_as_float(m0.z), __uint_as_float(m0.w));
        s1 = make_float4(__uint_as_float(m1.x) * sg, __uint_as_float(m1.y) * sg, __uint_as_float(m1.z), __uint_as_float(m1.w));
        mbar_wait(bars + BAR_V1, 0);
        TLC(21);
        epi_ab<0>(P, c, s0.x, s0.y, s1.x, s1.y, stg);
        epi_ab<1>(P, c, s0.x, s0.y, s1.x, s1.y, stg);
      }
      if (S == AB0 + 1) {
        epi_ab<2>(P, c, s0.x, s0.y, s1.x, s1.y, stg);
        epi_ab<3>(P, c, s0.x, s0.y, s1.x, s1.y, stg);
        fence_async_smem();
        bar_arrive(1, 288);
      }
    });
    TLC(3);
    static_for<16, 24>([&](auto S_) {
      constexpr int S = decltype(S_)::value;
      mma_step1<128, 1, S>(R, c);
      wg_wait<1>();
      release1<S - 1>(c);
      if (S == HA0) { reg_fence(Q); mbar_wait(bars + BAR_V2, 0); mbar_wait(bars + BAR_FREE, 0); epi_h<0, 0>(Q, c, s0.z, s0.w, s1.z, s1.w, stg); }
      if (S == HA1) epi_h<1, 1>(Q, c, s0.z, s0.w, s1.z, s1.w, stg);
      if (S == HA2) { epi_h<2, 2>(Q, c, s0.z, s0.w, s1.z, s1.w, stg); fence_async_smem(); bar_arrive(2, 288); }
    });
    TLC(4);
#pragma unroll
    for (int s = 24; s < 30; s++) {
      mma_step<128, 1>(Y, c, s % NST, (s / NST) & 1, s > 24);
      wg_wait<1>();
      release(c, (s - 1) % NST);
      if (s == HB0) { reg_fence(R); mbar_wait(bars + BAR_FREE, 1); epi_h<0, 3>(R, c, s0.z, s0.w, s1.z, s1.w, stg); }
      if (s == HB0 + 1) epi_h<1, 4>(R, c, s0.z, s0.w, s1.z, s1.w, stg);
      if (s == HB0 + 2) epi_h<2, 5>(R, c, s0.z, s0.w, s1.z, s1.w, stg);
      if (s == HB0 + 3) { epi_h<3, 6>(R, c, s0.z, s0.w, s1.z, s1.w, stg); fence_async_smem(); bar_arrive(3, 288); }
    }
    TLC(5);
    int st = 30 % NST, pst = 29 % NST; uint32_t ph = (30 / NST) & 1;
    const int ny = role ? 12 - NYB : 40 - NYB;
    for (int k = 0; k < ny; k++) {
      mma_step<128, 1>(Y, c, st, ph, 1);
      wg_wait<1>();
      release(c, pst);
      pst = st; if (++st == NST) { st = 0; ph ^= 1; }
    }
    TLC(6);
    const size_t ooff = (size_t)(rb * 128 + rl) * DM + cb * 128 + role * 64 + q8;
    if (role) {
      for (int k = 0; k < 28; k++) {
        mma_step<128, 1>(M, c, st, ph, k);
        wg_wait<1>();
        release(c, pst);
        pst = st; if (++st == NST) { st = 0; ph ^= 1; }
      }
      TLC(7);
      tail<1>(Y, M, c, p, tid, ooff);
    } else {
      TLC(7);
      tail<0>(Y, M, c, p, tid, ooff);
    }
  }
}

typedef CUresult (*EncFn)(CUtensorMap*, CUtensorMapDataType, cuuint32_t, void*, const cuuint64_t*, const cuuint64_t*, const cuuint32_t*,
                          const cuuint32_t*, CUtensorMapInterleave, CUtensorMapSwizzle, CUtensorMapL2promotion, CUtensorMapFloatOOBfill);

void make_map(EncFn enc, CUtensorMap* m, const void* ptr, int nd, const uint64_t* dims, const uint64_t* strides, const uint32_t* box,
              CUtensorMapSwizzle sw = CU_TENSOR_MAP_SWIZZLE_128B) {
  const cuuint32_t es[5] = {1, 1, 1, 1, 1};
  cuuint64_t d[5], s[5]; cuuint32_t b[5];
  for (int i = 0; i < nd; i++) { d[i] = dims[i]; b[i] = box[i]; if (i + 1 < nd) s[i] = strides[i]; }
  enc(m, CU_TENSOR_MAP_DATA_TYPE_BFLOAT16, nd, const_cast<void*>(ptr), d, s, b, es, CU_TENSOR_MAP_INTERLEAVE_NONE,
      sw, CU_TENSOR_MAP_L2_PROMOTION_L2_128B, CU_TENSOR_MAP_FLOAT_OOB_FILL_NONE);
}

}

extern "C" void kernel_launch(void* const* d_in, const int* in_sizes, int n_in, void* d_out, int out_size) {
  static Params prm;
  static const void* key[11];
  static EncFn enc = nullptr;
  bool same = enc != nullptr && key[10] == d_out;
  for (int i = 0; i < 10 && same; i++) same = key[i] == d_in[i];
  if (!same) {
    if (!enc) {
      cudaDriverEntryPointQueryResult q;
      cudaGetDriverEntryPoint("cuTensorMapEncodeTiled", reinterpret_cast<void**>(&enc), cudaEnableDefault, &q);
      cudaFuncSetAttribute(fused_kernel, cudaFuncAttributeMaxDynamicSharedMemorySize, SMEM_BYTES);
    }
    void *ab, *h;
    cudaGetSymbolAddress(&ab, g_ab);
    cudaGetSymbolAddress(&h, g_h);
    const uint32_t box2[2] = {64, 128}, box3[3] = {64, 64, 2}, box5[5] = {64, 2, 4, 4, 2};
    { const uint64_t d[2] = {DM, SEQ}, s[1] = {DM * 2}; make_map(enc, &prm.mx, d_in[0], 2, d, s, box2); }
    { const uint64_t d[2] = {SEQ, SEQ}, s[1] = {SEQ * 2}; make_map(enc, &prm.mcr, d_in[1], 2, d, s, box2); make_map(enc, &prm.mci, d_in[2], 2, d, s, box2); }
    { const uint64_t d[2] = {DM, DM}, s[1] = {DM * 2}; make_map(enc, &prm.mdre, d_in[3], 2, d, s, box2); make_map(enc, &prm.mdim, d_in[4], 2, d, s, box2); }
    { const uint64_t d[3] = {FF, DM, 2}, s[2] = {FF * 2, 128}; make_map(enc, &prm.mw1, d_in[6], 3, d, s, box3); }
    { const uint64_t d[3] = {64, 2 * SEQ, 8}, s[2] = {DM * 2, 128}; make_map(enc, &prm.mab, ab, 3, d, s, box3); }
    { const uint64_t d[2] = {FF, SEQ}, s[1] = {FF * 2}; make_map(enc, &prm.mh, h, 2, d, s, box2); }
    { const uint64_t d[5] = {DM, 2, 4, 4, FF / 32}, s[4] = {DM * 2, 8 * DM * 2, 2 * DM * 2, 32 * DM * 2}; make_map(enc, &prm.mw2, d_in[8], 5, d, s, box5); }
    const uint32_t boxs[2] = {32, 128};
    { const uint64_t d[2] = {DM, 2 * SEQ}, s[1] = {DM * 2}; make_map(enc, &prm.sab, ab, 2, d, s, boxs, CU_TENSOR_MAP_SWIZZLE_NONE); }
    { const uint64_t d[2] = {FF, SEQ}, s[1] = {FF * 2}; make_map(enc, &prm.sh, h, 2, d, s, boxs, CU_TENSOR_MAP_SWIZZLE_NONE); }
    prm.x = (const __nv_bfloat16*)d_in[0]; prm.dre = (const __nv_bfloat16*)d_in[3]; prm.dim = (const __nv_bfloat16*)d_in[4];
    prm.w1 = (const __nv_bfloat16*)d_in[6]; prm.b1 = (const __nv_bfloat16*)d_in[7]; prm.w2 = (const __nv_bfloat16*)d_in[8];
    prm.b2 = (const __nv_bfloat16*)d_in[9]; prm.out = (__nv_bfloat16*)d_out;
    for (int i = 0; i < 10; i++) key[i] = d_in[i];
    key[10] = d_out;
  }
  fused_kernel<<<128, 384, SMEM_BYTES>>>(prm);
}
```

```cpp
#include <cuda_runtime.h>
#include <cuda_bf16.h>
#include <cuda.h>
#include <stdint.h>

namespace {

constexpr int SEQ = 2048, DM = 512, FF = 1792;
constexpr int NST = 6;
constexpr int STB = 32768;
constexpr int OFF_STG = NST * STB;
constexpr int OFF_VH = OFF_STG + 32768;
constexpr int OFF_B2 = OFF_VH + 1792;
constexpr int OFF_BAR = OFF_B2 + 256;
constexpr int SMEM_BYTES = OFF_BAR + 288;
static_assert(SMEM_BYTES <= 232448, "smem");
constexpr int BAR_FULL = 0, BAR_EMPTY = 48, BAR_XF = 96, BAR_BF = 160, BAR_BE = 192, BAR_X16 = 224, BAR_V = 232, BAR_FREE = 240,
              BAR_E = 248, BAR_M = 256, BAR_Y = 264, BAR_OK = 272, OFF_EPOCH = 280;
__host__ __device__ constexpr int xslot(int k) { return (k < 4 ? k : 2 * k - 4) * 16384; }
__host__ __device__ constexpr int bslot(int i) { return (5 + 2 * i) * 16384; }
constexpr int S_S = 16, S_M = 48, S_Y = 62, S_END = 70;
__host__ __device__ constexpr int stage_of(int s) { return (s - S_S) % NST; }
__host__ __device__ constexpr int par_of(int s) { return ((s - S_S) / NST) & 1; }
constexpr int LAND_STAGE = stage_of(S_END - NST);
#define X16_AT 0
#define HS0 10
__host__ __device__ constexpr int units_done(int s) {
  const int n = s < HS0 ? 0 : s < S_S ? s - HS0 + 1 : (S_S - HS0) + ((s - S_S + 1) * 3) / 2;
  return n > 28 ? 28 : n;
}
__host__ __device__ constexpr int last_unit_step() { int s = 0; while (units_done(s) < 28) s++; return s; }
constexpr int S_ROLL = last_unit_step() + 1;

constexpr int C_DONE = 0, C_XN = 32, C_H = 64, C_UV = 64 + 16 * 32;

struct Params {
  CUtensorMap mx, mx16, sxn, mxn, mw1, mcr, mci, mh, sh, mw2, muv, suv, mdre, mdim;
  const __nv_bfloat16 *x, *w1, *b1, *b2;
  __nv_bfloat16* out;
};

__device__ __align__(1024) __nv_bfloat16 g_xn[SEQ * DM];
__device__ __align__(1024) __nv_bfloat16 g_uv[2 * SEQ * DM];
__device__ __align__(1024) __nv_bfloat16 g_h[SEQ * FF];
__device__ float2 g_stats[SEQ];
__device__ __align__(16) float g_csw[16 * FF];
__device__ unsigned g_cnt[64 + 32 * 32];
#define TLREC(ev) do {} while (0)
#define TLC(ev) do {} while (0)

__device__ __forceinline__ void mbar_init(uint32_t bar, uint32_t cnt) { asm volatile("mbarrier.init.shared::cta.b64 [%0], %1;" :: "r"(bar), "r"(cnt) : "memory"); }
__device__ __forceinline__ void mbar_expect_tx(uint32_t bar, uint32_t bytes) { asm volatile("mbarrier.arrive.expect_tx.shared::cta.b64 _, [%0], %1;" :: "r"(bar), "r"(bytes) : "memory"); }
__device__ __forceinline__ void mbar_arrive(uint32_t bar) { asm volatile("mbarrier.arrive.shared::cta.b64 _, [%0];" :: "r"(bar) : "memory"); }
__device__ __forceinline__ void mbar_arrive_cluster(uint32_t remote_bar) { asm volatile("mbarrier.arrive.shared::cluster.b64 _, [%0];" :: "r"(remote_bar) : "memory"); }
__device__ __forceinline__ uint32_t mapa(uint32_t addr, uint32_t cta) { uint32_t r; asm("mapa.shared::cluster.u32 %0, %1, %2;" : "=r"(r) : "r"(addr), "r"(cta)); return r; }
__device__ __forceinline__ bool mbar_try(uint32_t bar, uint32_t parity) {
  uint32_t ok;
  asm volatile("{\n.reg .pred p;\nmbarrier.try_wait.parity.shared::cta.b64 p, [%1], %2;\nselp.u32 %0, 1, 0, p;\n}" : "=r"(ok) : "r"(bar), "r"(parity) : "memory");
  return ok;
}
__device__ __forceinline__ void mbar_wait(uint32_t bar, uint32_t parity) {
  if (mbar_try(bar, parity)) return;
  for (uint32_t n = 0; n < (1u << 15); n++) if (mbar_try(bar, parity)) break;
}
__device__ __forceinline__ bool elect_one() {
  uint32_t p;
  asm volatile("{\n.reg .pred p;\nelect.sync _|p, 0xffffffff;\nselp.u32 %0, 1, 0, p;\n}" : "=r"(p));
  return p;
}
__device__ __forceinline__ void tma2d(uint32_t dst, const CUtensorMap* m, int c0, int c1, uint32_t bar) {
  asm volatile("cp.async.bulk.tensor.2d.shared::cluster.global.mbarrier::complete_tx::bytes [%0], [%1, {%3, %4}], [%2];"
    :: "r"(dst), "l"(m), "r"(bar), "r"(c0), "r"(c1) : "memory");
}
__device__ __forceinline__ void tma3d(uint32_t dst, const CUtensorMap* m, int c0, int c1, int c2, uint32_t bar) {
  asm volatile("cp.async.bulk.tensor.3d.shared::cluster.global.mbarrier::complete_tx::bytes [%0], [%1, {%3, %4, %5}], [%2];"
    :: "r"(dst), "l"(m), "r"(bar), "r"(c0), "r"(c1), "r"(c2) : "memory");
}
__device__ __forceinline__ void tma5d(uint32_t dst, const CUtensorMap* m, int c0, int c4, uint32_t bar) {
  asm volatile("cp.async.bulk.tensor.5d.shared::cluster.global.mbarrier::complete_tx::bytes [%0], [%1, {%3, %5, %5, %5, %4}], [%2];"
    :: "r"(dst), "l"(m), "r"(bar), "r"(c0), "r"(c4), "r"(0) : "memory");
}
__device__ __forceinline__ void tma_pf2d(const CUtensorMap* m, int c0, int c1) {
  asm volatile("cp.async.bulk.prefetch.tensor.2d.L2.global [%0, {%1, %2}];" :: "l"(m), "r"(c0), "r"(c1) : "memory");
}
__device__ __forceinline__ void wg_fence() { asm volatile("wgmma.fence.sync.aligned;" ::: "memory"); }
__device__ __forceinline__ void wg_commit() { asm volatile("wgmma.commit_group.sync.aligned;" ::: "memory"); }
template <int N> __device__ __forceinline__ void wg_wait() { asm volatile("wgmma.wait_group.sync.aligned %0;" :: "n"(N) : "memory"); }
template <int N> __device__ __forceinline__ void reg_fence(float (&d)[N]) {
#pragma unroll
  for (int i = 0; i < N; i++) asm volatile("" : "+f"(d[i]) :: "memory");
}
__device__ __forceinline__ void wgmma4_n128_tb0(float (&d)[64], uint32_t a, uint32_t b, int scale_d) {
  asm volatile("{\n.reg .pred p;\n.reg .b32 la, lb, hi;\n.reg .b64 da, db;\nsetp.ne.b32 p, %66, 0;\nmov.b32 hi, 0x40000040;\n"
    "add.u32 la, %64, 0;\nadd.u32 lb, %65, 0;\nmov.b64 da, {la, hi};\nmov.b64 db, {lb, hi};\n"
    "wgmma.mma_async.sync.aligned.m64n128k16.f32.bf16.bf16 "
    "{%0, %1, %2, %3, %4, %5, %6, %7, %8, %9, %10, %11, %12, %13, %14, %15, %16, %17, %18, %19, %20, %21, %22, %23, %24, %25, %26, %27, %28, %29, %30, %31, %32, %33, %34, %35, %36, %37, %38, %39, %40, %41, %42, %43, %44, %45, %46, %47, %48, %49, %50, %51, %52, %53, %54, %55, %56, %57, %58, %59, %60, %61, %62, %63}, "
    "da, db, p, 1, 1, 0, 0;\n"
    "add.u32 la, %64, 2;\nadd.u32 lb, %65, 2;\nmov.b64 da, {la, hi};\nmov.b64 db, {lb, hi};\n"
    "wgmma.mma_async.sync.aligned.m64n128k16.f32.bf16.bf16 "
    "{%0, %1, %2, %3, %4, %5, %6, %7, %8, %9, %10, %11, %12, %13, %14, %15, %16, %17, %18, %19, %20, %21, %22, %23, %24, %25, %26, %27, %28, %29, %30, %31, %32, %33, %34, %35, %36, %37, %38, %39, %40, %41, %42, %43, %44, %45, %46, %47, %48, %49, %50, %51, %52, %53, %54, %55, %56, %57, %58, %59, %60, %61, %62, %63}, "
    "da, db, 1, 1, 1, 0, 0;\n"
    "add.u32 la, %64, 4;\nadd.u32 lb, %65, 4;\nmov.b64 da, {la, hi};\nmov.b64 db, {lb, hi};\n"
    "wgmma.mma_async.sync.aligned.m64n128k16.f32.bf16.bf16 "
    "{%0, %1, %2, %3, %4, %5, %6, %7, %8, %9, %10, %11, %12, %13, %14, %15, %16, %17, %18, %19, %20, %21, %22, %23, %24, %25, %26, %27, %28, %29, %30, %31, %32, %33, %34, %35, %36, %37, %38, %39, %40, %41, %42, %43, %44, %45, %46, %47, %48, %49, %50, %51, %52, %53, %54, %55, %56, %57, %58, %59, %60, %61, %62, %63}, "
    "da, db, 1, 1, 1, 0, 0;\n"
    "add.u32 la, %64, 6;\nadd.u32 lb, %65, 6;\nmov.b64 da, {la, hi};\nmov.b64 db, {lb, hi};\n"
    "wgmma.mma_async.sync.aligned.m64n128k16.f32.bf16.bf16 "
    "{%0, %1, %2, %3, %4, %5, %6, %7, %8, %9, %10, %11, %12, %13, %14, %15, %16, %17, %18, %19, %20, %21, %22, %23, %24, %25, %26, %27, %28, %29, %30, %31, %32, %33, %34, %35, %36, %37, %38, %39, %40, %41, %42, %43, %44, %45, %46, %47, %48, %49, %50, %51, %52, %53, %54, %55, %56, %57, %58, %59, %60, %61, %62, %63}, "
    "da, db, 1, 1, 1, 0, 0;\n"
    "}\n"
    : "+f"(d[0]), "+f"(d[1]), "+f"(d[2]), "+f"(d[3]), "+f"(d[4]), "+f"(d[5]), "+f"(d[6]), "+f"(d[7]), "+f"(d[8]), "+f"(d[9]), "+f"(d[10]), "+f"(d[11]), "+f"(d[12]), "+f"(d[13]), "+f"(d[14]), "+f"(d[15]), "+f"(d[16]), "+f"(d[17]), "+f"(d[18]), "+f"(d[19]), "+f"(d[20]), "+f"(d[21]), "+f"(d[22]), "+f"(d[23]), "+f"(d[24]), "+f"(d[25]), "+f"(d[26]), "+f"(d[27]), "+f"(d[28]), "+f"(d[29]), "+f"(d[30]), "+f"(d[31]), "+f"(d[32]), "+f"(d[33]), "+f"(d[34]), "+f"(d[35]), "+f"(d[36]), "+f"(d[37]), "+f"(d[38]), "+f"(d[39]), "+f"(d[40]), "+f"(d[41]), "+f"(d[42]), "+f"(d[43]), "+f"(d[44]), "+f"(d[45]), "+f"(d[46]), "+f"(d[47]), "+f"(d[48]), "+f"(d[49]), "+f"(d[50]), "+f"(d[51]), "+f"(d[52]), "+f"(d[53]), "+f"(d[54]), "+f"(d[55]), "+f"(d[56]), "+f"(d[57]), "+f"(d[58]), "+f"(d[59]), "+f"(d[60]), "+f"(d[61]), "+f"(d[62]), "+f"(d[63])
    : "r"(a), "r"(b), "r"(scale_d));
}
__device__ __forceinline__ void wgmma4_n128_tb1(float (&d)[64], uint32_t a, uint32_t b, int scale_d) {
  asm volatile("{\n.reg .pred p;\n.reg .b32 la, lb, hi;\n.reg .b64 da, db;\nsetp.ne.b32 p, %66, 0;\nmov.b32 hi, 0x40000040;\n"
    "add.u32 la, %64, 0;\nadd.u32 lb, %65, 0;\nmov.b64 da, {la, hi};\nmov.b64 db, {lb, hi};\n"
    "wgmma.mma_async.sync.aligned.m64n128k16.f32.bf16.bf16 "
    "{%0, %1, %2, %3, %4, %5, %6, %7, %8, %9, %10, %11, %12, %13, %14, %15, %16, %17, %18, %19, %20, %21, %22, %23, %24, %25, %26, %27, %28, %29, %30, %31, %32, %33, %34, %35, %36, %37, %38, %39, %40, %41, %42, %43, %44, %45, %46, %47, %48, %49, %50, %51, %52, %53, %54, %55, %56, %57, %58, %59, %60, %61, %62, %63}, "
    "da, db, p, 1, 1, 0, 1;\n"
    "add.u32 la, %64, 2;\nadd.u32 lb, %65, 128;\nmov.b64 da, {la, hi};\nmov.b64 db, {lb, hi};\n"
    "wgmma.mma_async.sync.aligned.m64n128k16.f32.bf16.bf16 "
    "{%0, %1, %2, %3, %4, %5, %6, %7, %8, %9, %10, %11, %12, %13, %14, %15, %16, %17, %18, %19, %20, %21, %22, %23, %24, %25, %26, %27, %28, %29, %30, %31, %32, %33, %34, %35, %36, %37, %38, %39, %40, %41, %42, %43, %44, %45, %46, %47, %48, %49, %50, %51, %52, %53, %54, %55, %56, %57, %58, %59, %60, %61, %62, %63}, "
    "da, db, 1, 1, 1, 0, 1;\n"
    "add.u32 la, %64, 4;\nadd.u32 lb, %65, 256;\nmov.b64 da, {la, hi};\nmov.b64 db, {lb, hi};\n"
    "wgmma.mma_async.sync.aligned.m64n128k16.f32.bf16.bf16 "
    "{%0, %1, %2, %3, %4, %5, %6, %7, %8, %9, %10, %11, %12, %13, %14, %15, %16, %17, %18, %19, %20, %21, %22, %23, %24, %25, %26, %27, %28, %29, %30, %31, %32, %33, %34, %35, %36, %37, %38, %39, %40, %41, %42, %43, %44, %45, %46, %47, %48, %49, %50, %51, %52, %53, %54, %55, %56, %57, %58, %59, %60, %61, %62, %63}, "
    "da, db, 1, 1, 1, 0, 1;\n"
    "add.u32 la, %64, 6;\nadd.u32 lb, %65, 384;\nmov.b64 da, {la, hi};\nmov.b64 db, {lb, hi};\n"
    "wgmma.mma_async.sync.aligned.m64n128k16.f32.bf16.bf16 "
    "{%0, %1, %2, %3, %4, %5, %6, %7, %8, %9, %10, %11, %12, %13, %14, %15, %16, %17, %18, %19, %20, %21, %22, %23, %24, %25, %26, %27, %28, %29, %30, %31, %32, %33, %34, %35, %36, %37, %38, %39, %40, %41, %42, %43, %44, %45, %46, %47, %48, %49, %50, %51, %52, %53, %54, %55, %56, %57, %58, %59, %60, %61, %62, %63}, "
    "da, db, 1, 1, 1, 0, 1;\n"
    "}\n"
    : "+f"(d[0]), "+f"(d[1]), "+f"(d[2]), "+f"(d[3]), "+f"(d[4]), "+f"(d[5]), "+f"(d[6]), "+f"(d[7]), "+f"(d[8]), "+f"(d[9]), "+f"(d[10]), "+f"(d[11]), "+f"(d[12]), "+f"(d[13]), "+f"(d[14]), "+f"(d[15]), "+f"(d[16]), "+f"(d[17]), "+f"(d[18]), "+f"(d[19]), "+f"(d[20]), "+f"(d[21]), "+f"(d[22]), "+f"(d[23]), "+f"(d[24]), "+f"(d[25]), "+f"(d[26]), "+f"(d[27]), "+f"(d[28]), "+f"(d[29]), "+f"(d[30]), "+f"(d[31]), "+f"(d[32]), "+f"(d[33]), "+f"(d[34]), "+f"(d[35]), "+f"(d[36]), "+f"(d[37]), "+f"(d[38]), "+f"(d[39]), "+f"(d[40]), "+f"(d[41]), "+f"(d[42]), "+f"(d[43]), "+f"(d[44]), "+f"(d[45]), "+f"(d[46]), "+f"(d[47]), "+f"(d[48]), "+f"(d[49]), "+f"(d[50]), "+f"(d[51]), "+f"(d[52]), "+f"(d[53]), "+f"(d[54]), "+f"(d[55]), "+f"(d[56]), "+f"(d[57]), "+f"(d[58]), "+f"(d[59]), "+f"(d[60]), "+f"(d[61]), "+f"(d[62]), "+f"(d[63])
    : "r"(a), "r"(b), "r"(scale_d));
}
__device__ __forceinline__ void wgmma4_n96_tb1(float (&d)[48], uint32_t a, uint32_t b, int scale_d) {
  asm volatile("{\n.reg .pred p;\n.reg .b32 la, lb, hi;\n.reg .b64 da, db;\nsetp.ne.b32 p, %50, 0;\nmov.b32 hi, 0x40000040;\n"
    "add.u32 la, %48, 0;\nadd.u32 lb, %49, 0;\nmov.b64 da, {la, hi};\nmov.b64 db, {lb, hi};\n"
    "wgmma.mma_async.sync.aligned.m64n96k16.f32.bf16.bf16 "
    "{%0, %1, %2, %3, %4, %5, %6, %7, %8, %9, %10, %11, %12, %13, %14, %15, %16, %17, %18, %19, %20, %21, %22, %23, %24, %25, %26, %27, %28, %29, %30, %31, %32, %33, %34, %35, %36, %37, %38, %39, %40, %41, %42, %43, %44, %45, %46, %47}, "
    "da, db, p, 1, 1, 0, 1;\n"
    "add.u32 la, %48, 2;\nadd.u32 lb, %49, 128;\nmov.b64 da, {la, hi};\nmov.b64 db, {lb, hi};\n"
    "wgmma.mma_async.sync.aligned.m64n96k16.f32.bf16.bf16 "
    "{%0, %1, %2, %3, %4, %5, %6, %7, %8, %9, %10, %11, %12, %13, %14, %15, %16, %17, %18, %19, %20, %21, %22, %23, %24, %25, %26, %27, %28, %29, %30, %31, %32, %33, %34, %35, %36, %37, %38, %39, %40, %41, %42, %43, %44, %45, %46, %47}, "
    "da, db, 1, 1, 1, 0, 1;\n"
    "add.u32 la, %48, 4;\nadd.u32 lb, %49, 256;\nmov.b64 da, {la, hi};\nmov.b64 db, {lb, hi};\n"
    "wgmma.mma_async.sync.aligned.m64n96k16.f32.bf16.bf16 "
    "{%0, %1, %2, %3, %4, %5, %6, %7, %8, %9, %10, %11, %12, %13, %14, %15, %16, %17, %18, %19, %20, %21, %22, %23, %24, %25, %26, %27, %28, %29, %30, %31, %32, %33, %34, %35, %36, %37, %38, %39, %40, %41, %42, %43, %44, %45, %46, %47}, "
    "da, db, 1, 1, 1, 0, 1;\n"
    "add.u32 la, %48, 6;\nadd.u32 lb, %49, 384;\nmov.b64 da, {la, hi};\nmov.b64 db, {lb, hi};\n"
    "wgmma.mma_async.sync.aligned.m64n96k16.f32.bf16.bf16 "
    "{%0, %1, %2, %3, %4, %5, %6, %7, %8, %9, %10, %11, %12, %13, %14, %15, %16, %17, %18, %19, %20, %21, %22, %23, %24, %25, %26, %27, %28, %29, %30, %31, %32, %33, %34, %35, %36, %37, %38, %39, %40, %41, %42, %43, %44, %45, %46, %47}, "
    "da, db, 1, 1, 1, 0, 1;\n"
    "}\n"
    : "+f"(d[0]), "+f"(d[1]), "+f"(d[2]), "+f"(d[3]), "+f"(d[4]), "+f"(d[5]), "+f"(d[6]), "+f"(d[7]), "+f"(d[8]), "+f"(d[9]), "+f"(d[10]), "+f"(d[11]), "+f"(d[12]), "+f"(d[13]), "+f"(d[14]), "+f"(d[15]), "+f"(d[16]), "+f"(d[17]), "+f"(d[18]), "+f"(d[19]), "+f"(d[20]), "+f"(d[21]), "+f"(d[22]), "+f"(d[23]), "+f"(d[24]), "+f"(d[25]), "+f"(d[26]), "+f"(d[27]), "+f"(d[28]), "+f"(d[29]), "+f"(d[30]), "+f"(d[31]), "+f"(d[32]), "+f"(d[33]), "+f"(d[34]), "+f"(d[35]), "+f"(d[36]), "+f"(d[37]), "+f"(d[38]), "+f"(d[39]), "+f"(d[40]), "+f"(d[41]), "+f"(d[42]), "+f"(d[43]), "+f"(d[44]), "+f"(d[45]), "+f"(d[46]), "+f"(d[47])
    : "r"(a), "r"(b), "r"(scale_d));
}

__device__ __forceinline__ void bar_arrive(int id, int n) { asm volatile("bar.arrive %0, %1;" :: "r"(id), "r"(n) : "memory"); }
__device__ __forceinline__ void bar_sync(int id, int n) { asm volatile("bar.sync %0, %1;" :: "r"(id), "r"(n) : "memory"); }
__device__ __forceinline__ unsigned ld_rlx(const unsigned* p) { unsigned v; asm volatile("ld.relaxed.gpu.global.u32 %0, [%1];" : "=r"(v) : "l"(p) : "memory"); return v; }
__device__ __forceinline__ void red_add(unsigned* p) { asm volatile("red.relaxed.gpu.global.add.u32 [%0], 1;" :: "l"(p) : "memory"); }
__device__ __forceinline__ void wait_cnt(const unsigned* p, unsigned target) {
  for (uint32_t n = 0; n < (1u << 14); n++) if ((int)(ld_rlx(p) - target) >= 0) break;
}
__device__ __forceinline__ float bf_lo(uint32_t v) { return __uint_as_float(v << 16); }
__device__ __forceinline__ float bf_hi(uint32_t v) { return __uint_as_float(v & 0xffff0000u); }
__device__ __forceinline__ uint32_t pack2(float lo, float hi) { uint32_t r; asm("cvt.rn.bf16x2.f32 %0, %1, %2;" : "=r"(r) : "f"(hi), "f"(lo)); return r; }
__device__ __forceinline__ uint32_t pack2v(float lo, float hi) { uint32_t r; asm volatile("cvt.rn.bf16x2.f32 %0, %1, %2;" : "=r"(r) : "f"(hi), "f"(lo)); return r; }
__device__ __forceinline__ float bfr(float v) { return __bfloat162float(__float2bfloat16_rn(v)); }
__device__ __forceinline__ uint32_t tagf(float v, uint32_t tag) { return (__float_as_uint(v) & ~3u) | tag; }
template <int OFF> __device__ __forceinline__ uint4 ld_msg(const void* p) { uint4 v; asm volatile("ld.relaxed.gpu.global.v4.u32 {%0,%1,%2,%3}, [%4 + %5];" : "=r"(v.x), "=r"(v.y), "=r"(v.z), "=r"(v.w) : "l"(p), "n"(OFF) : "memory"); return v; }
__device__ __forceinline__ void st_msg(void* p, uint32_t a, uint32_t b, uint32_t c, uint32_t d) { asm volatile("st.relaxed.gpu.global.v4.u32 [%0], {%1,%2,%3,%4};" :: "l"(p), "r"(a), "r"(b), "r"(c), "r"(d) : "memory"); }
__device__ __forceinline__ uint32_t stale(const uint4& v, uint32_t tag) { return ((v.x ^ tag) | (v.y ^ tag) | (v.z ^ tag) | (v.w ^ tag)) & 3u; }
__device__ __forceinline__ void sts4(uint32_t a, uint32_t x, uint32_t y, uint32_t z, uint32_t w) { asm volatile("st.shared.v4.u32 [%0], {%1,%2,%3,%4};" :: "r"(a), "r"(x), "r"(y), "r"(z), "r"(w) : "memory"); }
__device__ __forceinline__ void tma_st2d(const CUtensorMap* m, uint32_t src, int c0, int c1) {
  asm volatile("cp.async.bulk.tensor.2d.global.shared::cta.bulk_group [%0, {%2, %3}], [%1];" :: "l"(m), "r"(src), "r"(c0), "r"(c1) : "memory");
}
__device__ __forceinline__ void tma_st3d(const CUtensorMap* m, uint32_t src, int c0, int c1, int c2) {
  asm volatile("cp.async.bulk.tensor.3d.global.shared::cta.bulk_group [%0, {%2, %3, %4}], [%1];" :: "l"(m), "r"(src), "r"(c0), "r"(c1), "r"(c2) : "memory");
}
__device__ __forceinline__ float tanh_f(float v) { float r; asm("tanh.approx.f32 %0, %1;" : "=f"(r) : "f"(v)); return r; }
__device__ __forceinline__ float gelu_half(float hf) {
  const float k0 = 2.0f * 0.7978845608028654f, k1 = 8.0f * 0.7978845608028654f * 0.044715f;
  return fmaf(hf, tanh_f(hf * fmaf(hf * hf, k1, k0)), hf);
}
__device__ __forceinline__ uint2 ld_msg2(const void* p) { uint2 v; asm volatile("ld.relaxed.gpu.global.v2.u32 {%0,%1}, [%2];" : "=r"(v.x), "=r"(v.y) : "l"(p) : "memory"); return v; }
__device__ __forceinline__ void fence_async_smem() { asm volatile("fence.proxy.async.shared::cta;" ::: "memory"); }
template <int OFF> __device__ __forceinline__ uint4 ldg_nc(const void* p) { uint4 v; asm volatile("ld.global.nc.v4.u32 {%0,%1,%2,%3}, [%4 + %5];" : "=r"(v.x), "=r"(v.y), "=r"(v.z), "=r"(v.w) : "l"(p), "n"(OFF)); return v; }
__device__ __forceinline__ void stg4(void* p, uint32_t a, uint32_t b, uint32_t c, uint32_t d) { asm volatile("st.global.v4.u32 [%0], {%1,%2,%3,%4};" :: "l"(p), "r"(a), "r"(b), "r"(c), "r"(d) : "memory"); }
__device__ __forceinline__ float4 lds4f(uint32_t a) { float4 v; asm volatile("ld.shared.v4.f32 {%0,%1,%2,%3}, [%4];" : "=f"(v.x), "=f"(v.y), "=f"(v.z), "=f"(v.w) : "r"(a)); return v; }
__device__ __forceinline__ uint4 lds4u(uint32_t a) { uint4 v; asm volatile("ld.shared.v4.u32 {%0,%1,%2,%3}, [%4];" : "=r"(v.x), "=r"(v.y), "=r"(v.z), "=r"(v.w) : "r"(a) : "memory"); return v; }
__device__ __forceinline__ float2 lds2f(uint32_t a) { float2 v; asm volatile("ld.shared.v2.f32 {%0,%1}, [%2];" : "=f"(v.x), "=f"(v.y) : "r"(a)); return v; }
__device__ __forceinline__ void st_async4(uint32_t raddr, uint32_t a, uint32_t b, uint32_t c, uint32_t d, uint32_t rbar) {
  asm volatile("st.async.weak.shared::cluster.mbarrier::complete_tx::bytes.v4.b32 [%0], {%1,%2,%3,%4}, [%5];"
    :: "r"(raddr), "r"(a), "r"(b), "r"(c), "r"(d), "r"(rbar) : "memory");
}

struct Ctx {
  uint32_t sm;
  uint32_t da;
  uint32_t db;
  bool lead;
};
template <int V> struct IC { static constexpr int value = V; };
template <int S0, int S1, class F>
__device__ __forceinline__ void static_for(F&& f) {
  if constexpr (S0 < S1) { f(IC<S0>{}); static_for<S0 + 1, S1>(f); }
}
template <int N, int TB>
__device__ __forceinline__ void mma_issue(float (&acc)[N / 2], const Ctx& c, uint32_t offa, uint32_t offb, int accum) {
  const uint32_t a = c.da + (offa >> 4), b = c.db + (offb >> 4) + (TB ? (512u << 16) : (1u << 16));
  wg_fence();
  if constexpr (N == 128 && TB == 0) wgmma4_n128_tb0(acc, a, b, accum);
  if constexpr (N == 128 && TB == 1) wgmma4_n128_tb1(acc, a, b, accum);
  if constexpr (N == 96) wgmma4_n96_tb1(acc, a, b, accum);
  wg_commit();
}
template <int N, int S>
__device__ __forceinline__ void step1(float (&acc)[N / 2], const Ctx& c) {
  if (S < 8) mbar_wait(c.sm + OFF_BAR + BAR_XF + 8 * S, 0);
  mbar_wait(c.sm + OFF_BAR + BAR_BF + 8 * (S & 3), (S >> 2) & 1);
  mma_issue<N, 1>(acc, c, xslot(S & 7), bslot(S & 3), (S & 7) != 0);
}
template <int TB>
__device__ __forceinline__ void step2(float (&acc)[64], const Ctx& c, int st, uint32_t ph, int accum) {
  mbar_wait(c.sm + OFF_BAR + BAR_FULL + 8 * st, ph);
  mma_issue<128, TB>(acc, c, st * STB, st * STB + 16384, accum);
}
__device__ __forceinline__ void release2(const Ctx& c, int st) {
  if (c.lead) mbar_arrive(c.sm + OFF_BAR + BAR_EMPTY + 8 * st);
}
template <int S>
__device__ __forceinline__ void release(const Ctx& c) {
  if constexpr (S < S_S) {
    if (c.lead) {
      if constexpr (S < 12) mbar_arrive(c.sm + OFF_BAR + BAR_BE + 8 * (S & 3));
      if constexpr (S == 9) mbar_arrive(c.sm + OFF_BAR + BAR_EMPTY);
      if constexpr (S >= 11) mbar_arrive(c.sm + OFF_BAR + BAR_EMPTY + 8 * (S - 10));
    }
  } else if constexpr (S < S_END - NST) {
    release2(c, stage_of(S));
  }
}

struct HEpi { float a0, b0, a1, b1; uint32_t vec, stg, never; uint32_t w0[4], w1[4]; };
template <int G, int I, int VG, int NA>
__device__ __forceinline__ void h_unit(const float (&acc)[NA], HEpi& e) {
  const float4 v = lds4f(e.vec + (16 * VG + 4 * I) * 16);
  const int r = 4 * (4 * G + I);
  e.w0[I] = pack2v(gelu_half(fmaf(e.a0, acc[r], fmaf(e.b0, v.x, v.z))), gelu_half(fmaf(e.a0, acc[r + 1], fmaf(e.b0, v.y, v.w))));
  e.w1[I] = pack2v(gelu_half(fmaf(e.a1, acc[r + 2], fmaf(e.b1, v.x, v.z))), gelu_half(fmaf(e.a1, acc[r + 3], fmaf(e.b1, v.y, v.w))));
  if (I < 3)
    asm volatile("{\n.reg .pred p;\nsetp.ne.u32 p, %0, 0;\n@p st.shared.v2.u32 [%1], {%2, %3};\n}" :: "r"(e.never), "r"(e.stg), "r"(e.w0[I]), "r"(e.w1[I]) : "memory");
  if (I == 3) {
    sts4(e.stg + G * 8192, e.w0[0], e.w0[1], e.w0[2], e.w0[3]);
    sts4(e.stg + G * 8192 + 512, e.w1[0], e.w1[1], e.w1[2], e.w1[3]);
  }
}

__global__ void __cluster_dims__(2, 1, 1) __launch_bounds__(384, 1) fused_kernel(const __grid_constant__ Params p) {
  extern __shared__ __align__(1024) uint8_t smem_raw[];
  const uint32_t sm = (uint32_t)__cvta_generic_to_shared(smem_raw);
  const int tid = threadIdx.x, lane = tid & 31;
  const int warp = __shfl_sync(0xffffffffu, tid >> 5, 0);
  int lc;
  {
    const int c = blockIdx.x >> 1;
    if (c < 4) lc = 4 + c;
    else if (c < 36) lc = ((c - 4) & 7) * 8 + ((c - 4) >> 3);
    else lc = (1 + (c - 36) % 7) * 8 + 4 + (c - 36) / 7;
  }
  const int rk = blockIdx.x & 1, cb = lc & 3, rb = lc >> 2, j = cb * 2 + rk;
  const int row0 = rb * 128;
  const uint32_t bars = sm + OFF_BAR;
  TLC(0);
#define EPOCH() mbar_wait(bars + BAR_E, 0); unsigned epoch; asm volatile("ld.shared.u32 %0, [%1];" : "=r"(epoch) : "r"(bars + OFF_EPOCH) : "memory"); const uint32_t tag = epoch & 3
  if (warp >= 8) {
    asm volatile("setmaxnreg.dec.sync.aligned.u32 88;");
    if (warp == 8) {
      if (elect_one()) {
        for (int s = 0; s < 8; s++) mbar_init(bars + BAR_XF + 8 * s, 1);
        for (int s = 0; s < 4; s++) { mbar_init(bars + BAR_BF + 8 * s, 1); mbar_init(bars + BAR_BE + 8 * s, 8); }
        mbar_init(bars + BAR_X16, 1);
        fence_async_smem();
        for (int k = 0; k < 8; k++) {
          mbar_expect_tx(bars + BAR_XF + 8 * k, 16384);
          tma2d(sm + xslot(k), &p.mx, k * 64, row0, bars + BAR_XF + 8 * k);
          if (k < 4) {
            mbar_expect_tx(bars + BAR_BF + 8 * k, 16384);
            tma3d(sm + bslot(k), &p.mw1, j * 224 + 96, k * 64, 0, bars + BAR_BF + 8 * k);
          }
          if (k == X16_AT) {
            mbar_expect_tx(bars + BAR_X16, 16384);
            tma3d(sm + OFF_STG, &p.mx16, 0, row0 + j * 16, 0, bars + BAR_X16);
          }
        }
        for (int s = 0; s < NST; s++) { mbar_init(bars + BAR_FULL + 8 * s, 1); mbar_init(bars + BAR_EMPTY + 8 * s, 8); }
        mbar_init(bars + BAR_V, 2); mbar_init(bars + BAR_FREE, 1); mbar_init(bars + BAR_E, 1);
        mbar_init(bars + BAR_M, 1); mbar_init(bars + BAR_Y, 1); mbar_init(bars + BAR_OK, 8);
        asm volatile("fence.mbarrier_init.release.cluster;" ::: "memory");
        fence_async_smem();
        mbar_expect_tx(bars + BAR_M, 32768);
        mbar_expect_tx(bars + BAR_Y, 32768);
      }
      __syncwarp();
      __syncthreads();
      asm volatile("barrier.cluster.arrive.relaxed.aligned;" ::: "memory");
      if (elect_one()) {
        const CUtensorMap* mc = rk ? &p.mci : &p.mcr;
        const CUtensorMap* md = rk ? &p.mdim : &p.mdre;
        asm volatile("prefetch.tensormap [%0];" :: "l"(mc) : "memory");
        asm volatile("prefetch.tensormap [%0];" :: "l"(&p.mxn) : "memory");
        asm volatile("prefetch.tensormap [%0];" :: "l"(&p.mh) : "memory");
        asm volatile("prefetch.tensormap [%0];" :: "l"(&p.mw2) : "memory");
        asm volatile("prefetch.tensormap [%0];" :: "l"(&p.muv) : "memory");
        asm volatile("prefetch.tensormap [%0];" :: "l"(md) : "memory");
        for (int k = 4; k < 16; k++) {
          const uint32_t fb = bars + BAR_BF + 8 * (k & 3);
          mbar_wait(bars + BAR_BE + 8 * (k & 3), ((k >> 2) & 1) ^ 1);
          mbar_expect_tx(fb, 16384);
          tma3d(sm + bslot(k & 3), &p.mw1, j * 224 + (k < 8 ? 96 : 0), (k & 7) * 64, 0, fb);
          if (k == 9) tma_pf2d(mc, cb * 64, row0);
        }
        int st = 0; uint32_t ph = 0;
#define P_ACQ() mbar_wait(bars + BAR_EMPTY + 8 * st, ph); const uint32_t fb = bars + BAR_FULL + 8 * st, sa = sm + st * STB, sb = sa + 16384; mbar_expect_tx(fb, STB)
#define P_ADV() if (++st == NST) { st = 0; ph ^= 1; }
        TLREC(11);
        EPOCH();
        wait_cnt(&g_cnt[C_XN], 128 * epoch);
        asm volatile("fence.proxy.async.global;" ::: "memory");
        TLREC(12);
        for (int k = 0; k < 32; k++) {
          P_ACQ(); tma2d(sa, mc, k * 64, row0, fb); tma3d(sb, &p.mxn, 0, k * 64, cb * 2, fb); P_ADV();
        }
        TLREC(13);
        wait_cnt(&g_cnt[C_H + rb * 32], 16 * epoch);
        asm volatile("fence.proxy.async.global;" ::: "memory");
        TLREC(14);
        const int n0 = cb * 128 + rk * 64, n1 = cb * 128 + (rk ^ 1) * 64;
        for (int k = rk * 14; k < rk * 14 + 14; k++) {
          P_ACQ(); tma2d(sa, &p.mh, k * 64, row0, fb); tma5d(sb, &p.mw2, n0, 2 * k, fb); tma5d(sb + 8192, &p.mw2, n1, 2 * k, fb); P_ADV();
        }
        TLREC(22);
        wait_cnt(&g_cnt[C_UV + rb * 32], 8 * epoch);
        asm volatile("fence.proxy.async.global;" ::: "memory");
        TLREC(23);
        red_add(&g_cnt[C_DONE]);
#pragma unroll 1
        for (int k = 0; k < 8; k++) {
          P_ACQ(); tma2d(sa, &p.muv, k * 64, rk * SEQ + row0, fb); tma5d(sb, md, k * 64, n0 >> 5, fb); tma5d(sb + 8192, md, k * 64, n1 >> 5, fb); P_ADV();
        }
      }
    } else if (warp == 9) {
      unsigned done0 = 0;
      if (lane == 0) done0 = ld_rlx(&g_cnt[C_DONE]);
      const int cl = lane < 28 ? lane : 27;
      const __nv_bfloat16* w = p.w1 + (size_t)(rb * 32) * FF + j * 224 + cl * 8;
      __syncthreads();
      asm volatile("barrier.cluster.arrive.relaxed.aligned;" ::: "memory");
      float s[8] = {0.f, 0.f, 0.f, 0.f, 0.f, 0.f, 0.f, 0.f};
#pragma unroll 1
      for (int hh = 0; hh < 2; hh++) {
        uint4 v[16];
        static_for<0, 16>([&](auto I) { v[decltype(I)::value] = ldg_nc<decltype(I)::value * FF * 2>(w + (size_t)hh * 16 * FF); });
        if (hh == 0 && lane == 0) { asm volatile("st.shared.u32 [%0], %1;" :: "r"(bars + OFF_EPOCH), "r"((done0 >> 7) + 1) : "memory"); mbar_arrive(bars + BAR_E); }
#pragma unroll
        for (int r = 0; r < 16; r++) {
          s[0] += bf_lo(v[r].x); s[1] += bf_hi(v[r].x); s[2] += bf_lo(v[r].y); s[3] += bf_hi(v[r].y);
          s[4] += bf_lo(v[r].z); s[5] += bf_hi(v[r].z); s[6] += bf_lo(v[r].w); s[7] += bf_hi(v[r].w);
        }
      }
      EPOCH();
      if (lane < 28) {
        float* dst = &g_csw[rb * FF + j * 224 + lane * 8];
        st_msg(dst, tagf(s[0], tag), tagf(s[1], tag), tagf(s[2], tag), tagf(s[3], tag));
        st_msg(dst + 4, tagf(s[4], tag), tagf(s[5], tag), tagf(s[6], tag), tagf(s[7], tag));
      }
      if (lane == 0) { TLREC(15); asm volatile("prefetch.tensormap [%0];" :: "l"(&p.sh) : "memory"); asm volatile("prefetch.tensormap [%0];" :: "l"(&p.suv) : "memory"); }
#pragma unroll 1
      for (int tile = 0; tile < 3; tile++) {
        bar_sync(1 + tile, 288);
        if (elect_one()) {
          TLREC(25 + tile);
          const CUtensorMap* m = tile == 2 ? &p.suv : &p.sh;
          const int c0 = tile == 2 ? cb * 128 : j * 224 + (tile == 0 ? 96 : 0), r0 = (tile == 2 ? rk * SEQ : 0) + row0;
#pragma unroll 1
          for (int g = 0; g < (tile == 1 ? 3 : 4); g++) tma_st2d(m, sm + OFF_STG + g * 8192, c0 + g * 32, r0);
          asm volatile("cp.async.bulk.commit_group;\ncp.async.bulk.wait_group.read 0;" ::: "memory");
          mbar_arrive(bars + BAR_FREE);
          asm volatile("cp.async.bulk.wait_group 0;" ::: "memory");
          red_add(&g_cnt[(tile == 2 ? C_UV : C_H) + rb * 32]);
          TLREC(17 + tile);
        }
        __syncwarp();
      }
    } else {
      __syncthreads();
      asm volatile("barrier.cluster.arrive.relaxed.aligned;" ::: "memory");
      if (warp == 10 && lane == 0) asm volatile("prefetch.tensormap [%0];" :: "l"(&p.sxn) : "memory");
      {
        const int r = (warp - 10) * 8 + ((lane >> 1) & 7);
        const uint32_t base = sm + OFF_STG + (lane >> 4) * 2048 + r * 128, sw = (((lane & 1) * 4) ^ (r & 7)) << 4;
        mbar_wait(bars + BAR_X16, 0);
        if (warp == 10 && lane == 0) TLREC(28);
        float s1 = 0.f;
#pragma unroll 1
        for (int it = 0; it < 4; it++) {
#pragma unroll
          for (int c = 0; c < 4; c++) {
            const uint4 t = lds4u(base + it * 4096 + (sw ^ (c << 4)));
            s1 += ((bf_lo(t.x) + bf_hi(t.x)) + (bf_lo(t.y) + bf_hi(t.y))) + ((bf_lo(t.z) + bf_hi(t.z)) + (bf_lo(t.w) + bf_hi(t.w)));
          }
        }
        s1 += __shfl_xor_sync(0xffffffffu, s1, 1); s1 += __shfl_xor_sync(0xffffffffu, s1, 16);
        const float mean = s1 * (1.0f / DM);
        float qa = 0.f, qb = 0.f;
#pragma unroll 1
        for (int it = 0; it < 4; it++) {
#pragma unroll
          for (int c = 0; c < 4; c++) {
            const uint4 t = lds4u(base + it * 4096 + (sw ^ (c << 4)));
            const uint32_t w[4] = {t.x, t.y, t.z, t.w};
#pragma unroll
            for (int i = 0; i < 4; i++) { const float a = bf_lo(w[i]) - mean, b = bf_hi(w[i]) - mean; qa = fmaf(a, a, qa); qb = fmaf(b, b, qb); }
          }
        }
        float q = qa + qb;
        q += __shfl_xor_sync(0xffffffffu, q, 1); q += __shfl_xor_sync(0xffffffffu, q, 16);
        const float m1 = bfr(mean), d1 = bfr(__fsqrt_rn(bfr(bfr(q * (1.0f / DM)) + 1e-5f))), i1 = __frcp_rn(d1);
        float s2 = 0.f; qa = 0.f; qb = 0.f;
#pragma unroll 1
        for (int it = 0; it < 4; it++) {
          uint32_t o[4][4];
#pragma unroll
          for (int c = 0; c < 4; c++) {
            const uint4 t = lds4u(base + it * 4096 + (sw ^ (c << 4)));
            const uint32_t w[4] = {t.x, t.y, t.z, t.w};
#pragma unroll
            for (int i = 0; i < 4; i++) {
              const uint32_t d = pack2(bf_lo(w[i]) - m1, bf_hi(w[i]) - m1);
              const uint32_t n = pack2(bf_lo(d) * i1, bf_hi(d) * i1);
              const float a = bf_lo(n), b = bf_hi(n);
              s2 += a + b; qa = fmaf(a, a, qa); qb = fmaf(b, b, qb);
              o[i][c] = n;
            }
          }
#pragma unroll
          for (int c = 0; c < 4; c++) sts4(base + it * 4096 + (sw ^ (c << 4)), o[c][0], o[c][1], o[c][2], o[c][3]);
        }
        fence_async_smem();
        bar_sync(4, 64);
        if (warp == 10 && lane == 0) {
          tma_st3d(&p.sxn, sm + OFF_STG, 0, row0 + j * 16, 0);
          asm volatile("cp.async.bulk.commit_group;" ::: "memory");
        }
        q = qa + qb;
        s2 += __shfl_xor_sync(0xffffffffu, s2, 1); q += __shfl_xor_sync(0xffffffffu, q, 1);
        s2 += __shfl_xor_sync(0xffffffffu, s2, 16); q += __shfl_xor_sync(0xffffffffu, q, 16);
        const float mean2 = s2 * (1.0f / DM), var2 = fmaxf(fmaf(q, 1.0f / DM, -mean2 * mean2), 0.f);
        const float m2 = bfr(mean2), d2 = bfr(__fsqrt_rn(bfr(bfr(var2) + 1e-5f))), i2 = 0.5f * __frcp_rn(d2);
        EPOCH();
        if ((lane & 17) == 0)
          asm volatile("st.relaxed.gpu.global.v2.u32 [%0], {%1,%2};" :: "l"(&g_stats[row0 + j * 16 + r]), "r"(tagf(i1 * i2, tag)), "r"(tagf(-(m1 * i1 + m2) * i2, tag)) : "memory");
        if (warp == 10 && lane == 0) {
          TLREC(29);
          asm volatile("cp.async.bulk.wait_group.read 0;" ::: "memory");
          mbar_arrive(bars + BAR_FREE);
          asm volatile("cp.async.bulk.wait_group 0;" ::: "memory");
          red_add(&g_cnt[C_XN]);
          TLREC(20);
        }
        __syncwarp();
      }
      EPOCH();
      const int cl = lane < 28 ? lane : 27;
      const int q = (warp - 10) * 28 + cl;
      const uint2 bb = *reinterpret_cast<const uint2*>(p.b1 + j * 224 + q * 4);
      if (warp == 11) {
        const uint32_t b2v = *reinterpret_cast<const uint32_t*>(p.b2 + cb * 128 + rk * 64 + lane * 2);
        *reinterpret_cast<float2*>(smem_raw + OFF_B2 + lane * 8) = make_float2(0.5f * bf_lo(b2v), 0.5f * bf_hi(b2v));
      }
      float4 acc;
      for (uint32_t n = 0; n < (1u << 14); n++) {
        uint32_t bad = 0;
        acc = make_float4(0.f, 0.f, 0.f, 0.f);
        uint4 m[16];
        static_for<0, 16>([&](auto I) { m[decltype(I)::value] = ld_msg<decltype(I)::value * FF * 4>(&g_csw[j * 224 + q * 4]); });
#pragma unroll
        for (int r = 0; r < 16; r++) {
          bad |= stale(m[r], tag);
          acc.x += __uint_as_float(m[r].x); acc.y += __uint_as_float(m[r].y); acc.z += __uint_as_float(m[r].z); acc.w += __uint_as_float(m[r].w);
        }
        if (!__any_sync(0xffffffffu, bad)) break;
      }
      if (lane < 28) {
        float4* s4 = reinterpret_cast<float4*>(smem_raw + OFF_VH);
        s4[q * 2] = make_float4(acc.x, acc.y, 0.5f * bf_lo(bb.x), 0.5f * bf_hi(bb.x));
        s4[q * 2 + 1] = make_float4(acc.z, acc.w, 0.5f * bf_lo(bb.y), 0.5f * bf_hi(bb.y));
      }
      __syncwarp();
      if (lane == 0) { mbar_arrive(bars + BAR_V); if (warp == 10) TLREC(24); }
    }
  } else {
    asm volatile("setmaxnreg.inc.sync.aligned.u32 208;");
    __syncthreads();
    asm volatile("barrier.cluster.arrive.relaxed.aligned;" ::: "memory");
    Ctx c; c.sm = sm; c.lead = lane == 0;
    c.da = (((sm + (warp >> 2) * 8192) & 0x3FFFF) >> 4) | (1u << 16); c.db = (sm & 0x3FFFF) >> 4;
    const int rl = warp * 16 + (lane >> 2);
    float Q[64], R[48], U[64], M[64], Y[64];
    HEpi e;
    e.vec = sm + OFF_VH + (lane & 3) * 16; e.stg = sm + OFF_STG + rl * 64 + (lane & 3) * 16;
    e.never = gridDim.y - 1;
    uint2 m0, m1;
    static_for<0, S_ROLL>([&](auto S_) {
      constexpr int S = decltype(S_)::value;
      if constexpr (S < 8) step1<128, S>(Q, c);
      else if constexpr (S < S_S) step1<96, S>(R, c);
      else step2<1>(U, c, stage_of(S), par_of(S), S > S_S);
      if (S == 0) TLC(1);
      if (S == HS0 - 1) { m0 = ld_msg2(&g_stats[row0 + rl]); m1 = ld_msg2(&g_stats[row0 + rl + 8]); }
      if constexpr (S > 0) { wg_wait<1>(); release<S - 1>(c); }
      if (S == 8) { reg_fence(Q); TLC(2); }
      if (S == S_S) { reg_fence(R); TLC(3); }
      if (S == HS0) {
        EPOCH();
        for (uint32_t n = 0; n < (1u << 14) && (((m0.x ^ tag) | (m0.y ^ tag) | (m1.x ^ tag) | (m1.y ^ tag)) & 3u); n++) {
          m0 = ld_msg2(&g_stats[row0 + rl]); m1 = ld_msg2(&g_stats[row0 + rl + 8]);
        }
        e.a0 = __uint_as_float(m0.x); e.b0 = __uint_as_float(m0.y); e.a1 = __uint_as_float(m1.x); e.b1 = __uint_as_float(m1.y);
        mbar_wait(bars + BAR_V, 0);
        TLC(21);
      }
      static_for<units_done(S - 1), units_done(S)>([&](auto U_) {
        constexpr int u = decltype(U_)::value;
        if (u == 3) mbar_wait(bars + BAR_FREE, 0);
        if (u == 19) mbar_wait(bars + BAR_FREE, 1);
        if constexpr (u < 16) h_unit<u / 4, u % 4, 3 + u / 4>(Q, e);
        else h_unit<(u - 16) / 4, u % 4, (u - 16) / 4>(R, e);
        if (u == 15 || u == 27) { fence_async_smem(); bar_arrive(u == 15 ? 1 : 2, 288); }
      });
    });
    TLC(4);
    int st = stage_of(S_ROLL), pst = stage_of(S_ROLL - 1); uint32_t ph = par_of(S_ROLL);
#pragma unroll 1
    for (int s = S_ROLL; s < S_M; s++) {
      step2<1>(U, c, st, ph, 1);
      wg_wait<1>();
      release2(c, pst);
      pst = st; if (++st == NST) { st = 0; ph ^= 1; }
    }
    TLC(5);
    step2<1>(M, c, stage_of(S_M), par_of(S_M), 0);
    wg_wait<1>();
    release<S_M - 1>(c);
    reg_fence(U);
    mbar_wait(bars + BAR_FREE, 0);
#pragma unroll
    for (int G = 0; G < 4; G++) {
      const int r = 16 * G;
      sts4(e.stg + G * 8192, pack2(U[r], U[r + 1]), pack2(U[r + 4], U[r + 5]), pack2(U[r + 8], U[r + 9]), pack2(U[r + 12], U[r + 13]));
      sts4(e.stg + G * 8192 + 512, pack2(U[r + 2], U[r + 3]), pack2(U[r + 6], U[r + 7]), pack2(U[r + 10], U[r + 11]), pack2(U[r + 14], U[r + 15]));
    }
    fence_async_smem();
    bar_arrive(3, 288);
    st = stage_of(S_M + 1); pst = stage_of(S_M); ph = par_of(S_M + 1);
#pragma unroll 1
    for (int s = S_M + 1; s < S_Y; s++) {
      step2<1>(M, c, st, ph, 1);
      wg_wait<1>();
      release2(c, pst);
      pst = st; if (++st == NST) { st = 0; ph ^= 1; }
    }
    TLC(6);
    const size_t ooff = (size_t)(row0 + rl) * DM + cb * 128 + rk * 64 + (lane & 3) * 8;
    const uint32_t mine = warp * 4096 + lane * 16, peer = rk ^ 1, sgn = rk ? 0x80008000u : 0u;
    uint4 g[4], xr[4];
    static_for<S_Y, S_END>([&](auto S_) {
      constexpr int S = decltype(S_)::value;
      step2<0>(Y, c, stage_of(S), par_of(S), S > S_Y);
      wg_wait<1>();
      release<S - 1>(c);
      if (S == S_Y) {
        reg_fence(M);
        asm volatile("barrier.cluster.wait.aligned;" ::: "memory");
        const uint32_t ra = mapa(sm + OFF_STG + mine, peer), rbar = mapa(bars + BAR_M, peer);
#pragma unroll
        for (int v = 0; v < 8; v++)
          st_async4(ra + v * 512, __float_as_uint(M[32 + 4 * v]), __float_as_uint(M[33 + 4 * v]), __float_as_uint(M[34 + 4 * v]), __float_as_uint(M[35 + 4 * v]), rbar);
        xr[0] = ldg_nc<0>(p.x + ooff); xr[1] = ldg_nc<16 * DM>(p.x + ooff);
        xr[2] = ldg_nc<64>(p.x + ooff); xr[3] = ldg_nc<16 * DM + 64>(p.x + ooff);
      }
      if (S == S_Y + 2) {
        mbar_wait(bars + BAR_M, 0);
#pragma unroll
        for (int v = 0; v < 8; v++) {
          const uint4 t = lds4u(sm + OFF_STG + mine + v * 512);
          M[4 * v] += __uint_as_float(t.x); M[4 * v + 1] += __uint_as_float(t.y); M[4 * v + 2] += __uint_as_float(t.z); M[4 * v + 3] += __uint_as_float(t.w);
        }
      }
      if (S == S_END - NST + 1 && c.lead) mbar_arrive_cluster(mapa(bars + BAR_OK, peer));
      if constexpr (S >= S_Y + 3 && S < S_Y + 7) {
        constexpr int G = (S - S_Y - 3) >> 1, H = (S - S_Y - 3) & 1;
        uint32_t w[4];
#pragma unroll
        for (int i = 0; i < 4; i++) {
          const float2 b = lds2f(sm + OFF_B2 + (32 * G + 8 * i) * 4 + (lane & 3) * 8);
          const int r = 4 * (4 * G + i) + 2 * H;
          const float z0 = fmaf(M[r], 0.5f, b.x), z1 = fmaf(M[r + 1], 0.5f, b.y);
          w[i] = pack2(fmaf(z0, tanh_f(z0), z0), fmaf(z1, tanh_f(z1), z1)) ^ sgn;
        }
        const uint32_t tb = sm + OFF_STG + warp * 4096 + (2 * G + H) * 512;
        __syncwarp();
        asm volatile("stmatrix.sync.aligned.m8n8.x4.shared.b16 [%0], {%1,%2,%3,%4};"
                     :: "r"(tb + (lane & 7) * 64 + (((lane >> 3) ^ ((lane >> 1) & 3)) << 4)), "r"(w[0]), "r"(w[1]), "r"(w[2]), "r"(w[3]) : "memory");
        __syncwarp();
        g[2 * G + H] = lds4u(tb + (lane >> 2) * 64 + (((lane & 3) ^ ((lane >> 3) & 3)) << 4));
      }
    });
    mbar_wait(bars + BAR_OK, 0);
    const uint32_t rl_ = mapa(sm + LAND_STAGE * STB + mine, peer), rlb = mapa(bars + BAR_Y, peer);
    TLC(7);
    wg_wait<0>();
    reg_fence(Y);
    TLC(8);
#pragma unroll
    for (int v = 0; v < 8; v++)
      st_async4(rl_ + v * 512, __float_as_uint(Y[32 + 4 * v]), __float_as_uint(Y[33 + 4 * v]), __float_as_uint(Y[34 + 4 * v]), __float_as_uint(Y[35 + 4 * v]), rlb);
    mbar_wait(bars + BAR_Y, 0);
    TLC(9);
#pragma unroll
    for (int G = 0; G < 2; G++) {
      uint32_t o0[4], o1[4];
      const uint32_t g0[4] = {g[2 * G].x, g[2 * G].y, g[2 * G].z, g[2 * G].w}, g1[4] = {g[2 * G + 1].x, g[2 * G + 1].y, g[2 * G + 1].z, g[2 * G + 1].w};
      const uint32_t x0[4] = {xr[2 * G].x, xr[2 * G].y, xr[2 * G].z, xr[2 * G].w}, x1[4] = {xr[2 * G + 1].x, xr[2 * G + 1].y, xr[2 * G + 1].z, xr[2 * G + 1].w};
#pragma unroll
      for (int i = 0; i < 4; i++) {
        const uint4 t = lds4u(sm + LAND_STAGE * STB + mine + (4 * G + i) * 512);
        const int a = 4 * (4 * G + i);
        o0[i] = pack2(fmaf(Y[a] - __uint_as_float(t.x), bf_lo(g0[i]), bf_lo(x0[i])), fmaf(Y[a + 1] - __uint_as_float(t.y), bf_hi(g0[i]), bf_hi(x0[i])));
        o1[i] = pack2(fmaf(Y[a + 2] - __uint_as_float(t.z), bf_lo(g1[i]), bf_lo(x1[i])), fmaf(Y[a + 3] - __uint_as_float(t.w), bf_hi(g1[i]), bf_hi(x1[i])));
      }
      stg4(p.out + ooff + 32 * G, o0[0], o0[1], o0[2], o0[3]);
      stg4(p.out + ooff + 32 * G + 8 * DM, o1[0], o1[1], o1[2], o1[3]);
    }
    TLC(10);
  }
}

typedef CUresult (*EncFn)(CUtensorMap*, CUtensorMapDataType, cuuint32_t, void*, const cuuint64_t*, const cuuint64_t*, const cuuint32_t*,
                          const cuuint32_t*, CUtensorMapInterleave, CUtensorMapSwizzle, CUtensorMapL2promotion, CUtensorMapFloatOOBfill);

void make_map(EncFn enc, CUtensorMap* m, const void* ptr, int nd, const uint64_t* dims, const uint64_t* strides, const uint32_t* box,
              CUtensorMapSwizzle sw = CU_TENSOR_MAP_SWIZZLE_128B) {
  const cuuint32_t es[5] = {1, 1, 1, 1, 1};
  cuuint64_t d[5], s[5]; cuuint32_t b[5];
  for (int i = 0; i < nd; i++) { d[i] = dims[i]; b[i] = box[i]; if (i + 1 < nd) s[i] = strides[i]; }
  enc(m, CU_TENSOR_MAP_DATA_TYPE_BFLOAT16, nd, const_cast<void*>(ptr), d, s, b, es, CU_TENSOR_MAP_INTERLEAVE_NONE,
      sw, CU_TENSOR_MAP_L2_PROMOTION_L2_128B, CU_TENSOR_MAP_FLOAT_OOB_FILL_NONE);
}

}

extern "C" void kernel_launch(void* const* d_in, const int* in_sizes, int n_in, void* d_out, int out_size) {
  static Params prm;
  static const void* key[11];
  static EncFn enc = nullptr;
  bool same = enc != nullptr && key[10] == d_out;
  for (int i = 0; i < 10 && same; i++) same = key[i] == d_in[i];
  if (!same) {
    if (!enc) {
      cudaDriverEntryPointQueryResult q;
      cudaGetDriverEntryPoint("cuTensorMapEncodeTiled", reinterpret_cast<void**>(&enc), cudaEnableDefault, &q);
      cudaFuncSetAttribute(fused_kernel, cudaFuncAttributeMaxDynamicSharedMemorySize, SMEM_BYTES);
    }
    void *xn, *uv, *h;
    cudaGetSymbolAddress(&xn, g_xn);
    cudaGetSymbolAddress(&uv, g_uv);
    cudaGetSymbolAddress(&h, g_h);
    const uint64_t R = DM * 2;
    const uint32_t box2[2] = {64, 128}, box3[3] = {64, 64, 2}, box5[5] = {64, 2, 4, 4, 2}, box16[3] = {64, 16, 8}, boxs[2] = {32, 128};
    { const uint64_t d[2] = {DM, SEQ}, s[1] = {R}; make_map(enc, &prm.mx, d_in[0], 2, d, s, box2); }
    { const uint64_t d[3] = {64, SEQ, 8}, s[2] = {R, 128};
      make_map(enc, &prm.mx16, d_in[0], 3, d, s, box16); make_map(enc, &prm.sxn, xn, 3, d, s, box16); make_map(enc, &prm.mxn, xn, 3, d, s, box3); }
    { const uint64_t d[2] = {SEQ, SEQ}, s[1] = {SEQ * 2}; make_map(enc, &prm.mcr, d_in[1], 2, d, s, box2); make_map(enc, &prm.mci, d_in[2], 2, d, s, box2); }
    { const uint64_t d[5] = {DM, 2, 4, 4, DM / 32}, s[4] = {R, 8 * R, 2 * R, 32 * R};
      make_map(enc, &prm.mdre, d_in[3], 5, d, s, box5); make_map(enc, &prm.mdim, d_in[4], 5, d, s, box5); }
    { const uint64_t d[3] = {FF, DM, 2}, s[2] = {FF * 2, 128}; make_map(enc, &prm.mw1, d_in[6], 3, d, s, box3); }
    { const uint64_t d[2] = {FF, SEQ}, s[1] = {FF * 2}; make_map(enc, &prm.mh, h, 2, d, s, box2); make_map(enc, &prm.sh, h, 2, d, s, boxs, CU_TENSOR_MAP_SWIZZLE_NONE); }
    { const uint64_t d[5] = {DM, 2, 4, 4, FF / 32}, s[4] = {R, 8 * R, 2 * R, 32 * R}; make_map(enc, &prm.mw2, d_in[8], 5, d, s, box5); }
    { const uint64_t d[2] = {DM, 2 * SEQ}, s[1] = {R}; make_map(enc, &prm.muv, uv, 2, d, s, box2); make_map(enc, &prm.suv, uv, 2, d, s, boxs, CU_TENSOR_MAP_SWIZZLE_NONE); }
    prm.x = (const __nv_bfloat16*)d_in[0]; prm.w1 = (const __nv_bfloat16*)d_in[6]; prm.b1 = (const __nv_bfloat16*)d_in[7];
    prm.b2 = (const __nv_bfloat16*)d_in[9]; prm.out = (__nv_bfloat16*)d_out;
    for (int i = 0; i < 10; i++) key[i] = d_in[i];
    key[10] = d_out;
  }
  fused_kernel<<<128, 384, SMEM_BYTES>>>(prm);
}
```

```cpp
#include <cuda_runtime.h>
#include <cuda_bf16.h>
#include <cuda.h>
#include <stdint.h>

namespace {

constexpr int SEQ = 2048, DM = 512, FF = 1792;
constexpr int NST = 6;
constexpr int STB = 32768;
constexpr int OFF_STG = NST * STB;
constexpr int OFF_VH = OFF_STG + 32768;
constexpr int OFF_B2 = OFF_VH + 1792;
constexpr int OFF_BAR = OFF_B2 + 256;
constexpr int SMEM_BYTES = OFF_BAR + 296;
static_assert(SMEM_BYTES <= 232448, "smem");
constexpr int BAR_FULL = 0, BAR_EMPTY = 48, BAR_XF = 96, BAR_BF = 160, BAR_BE = 192, BAR_X16 = 224, BAR_V = 232, BAR_FREE = 240,
              BAR_E = 248, BAR_M = 256, BAR_Y = 264, BAR_OK = 272, BAR_DEP = 280, OFF_EPOCH = 288;
__host__ __device__ constexpr int xslot(int k) { return (k < 4 ? k : 2 * k - 4) * 16384; }
__host__ __device__ constexpr int bslot(int i) { return (5 + 2 * i) * 16384; }
constexpr int S_S = 16, S_M = 48, S_Y = 62, S_END = 70;
__host__ __device__ constexpr int stage_of(int s) { return (s - S_S) % NST; }
__host__ __device__ constexpr int par_of(int s) { return ((s - S_S) / NST) & 1; }
constexpr int LAND_STAGE = stage_of(S_END - NST);
#define X16_AT 0
#define XS0 0
#define HS0 10
#define UNUM 1
#define UDEN 1
__host__ __device__ constexpr int units_done(int s) {
  const int n = s < HS0 ? 0 : s < S_S ? s - HS0 + 1 : (S_S - HS0) + ((s - S_S + 1) * UNUM) / UDEN;
  return n > 28 ? 28 : n;
}
__host__ __device__ constexpr int last_unit_step() { int s = 0; while (units_done(s) < 28) s++; return s; }
constexpr int S_ROLL = last_unit_step() + 1;

constexpr int C_DONE = 0, C_XN = 32, C_H = 64, C_UV = 64 + 16 * 32;

struct Params {
  CUtensorMap mx, mx16, sxn, mxn, mw1, mcr, mci, mh, sh, mw2, muv, suv, mdre, mdim;
  const __nv_bfloat16 *x, *w1, *b1, *b2;
  __nv_bfloat16* out;
};

__device__ __align__(1024) __nv_bfloat16 g_xn[SEQ * DM];
__device__ __align__(1024) __nv_bfloat16 g_uv[2 * SEQ * DM];
__device__ __align__(1024) __nv_bfloat16 g_h[SEQ * FF];
__device__ float2 g_stats[SEQ];
__device__ __align__(16) float g_csw[16 * FF];
__device__ unsigned g_cnt[64 + 32 * 32];
#define TLREC(ev) do {} while (0)
#define TLC(ev) do {} while (0)

__device__ __forceinline__ void mbar_init(uint32_t bar, uint32_t cnt) { asm volatile("mbarrier.init.shared::cta.b64 [%0], %1;" :: "r"(bar), "r"(cnt) : "memory"); }
__device__ __forceinline__ void mbar_expect_tx(uint32_t bar, uint32_t bytes) { asm volatile("mbarrier.arrive.expect_tx.shared::cta.b64 _, [%0], %1;" :: "r"(bar), "r"(bytes) : "memory"); }
__device__ __forceinline__ void mbar_arrive(uint32_t bar) { asm volatile("mbarrier.arrive.shared::cta.b64 _, [%0];" :: "r"(bar) : "memory"); }
__device__ __forceinline__ void mbar_arrive_cluster(uint32_t remote_bar) { asm volatile("mbarrier.arrive.shared::cluster.b64 _, [%0];" :: "r"(remote_bar) : "memory"); }
__device__ __forceinline__ uint32_t mapa(uint32_t addr, uint32_t cta) { uint32_t r; asm("mapa.shared::cluster.u32 %0, %1, %2;" : "=r"(r) : "r"(addr), "r"(cta)); return r; }
__device__ __forceinline__ bool mbar_try(uint32_t bar, uint32_t parity) {
  uint32_t ok;
  asm volatile("{\n.reg .pred p;\nmbarrier.try_wait.parity.shared::cta.b64 p, [%1], %2;\nselp.u32 %0, 1, 0, p;\n}" : "=r"(ok) : "r"(bar), "r"(parity) : "memory");
  return ok;
}
__device__ __forceinline__ void mbar_wait(uint32_t bar, uint32_t parity) {
  if (mbar_try(bar, parity)) return;
  for (uint32_t n = 0; n < (1u << 15); n++) if (mbar_try(bar, parity)) break;
}
__device__ __forceinline__ bool elect_one() {
  uint32_t p;
  asm volatile("{\n.reg .pred p;\nelect.sync _|p, 0xffffffff;\nselp.u32 %0, 1, 0, p;\n}" : "=r"(p));
  return p;
}
__device__ __forceinline__ void tma2d(uint32_t dst, const CUtensorMap* m, int c0, int c1, uint32_t bar) {
  asm volatile("cp.async.bulk.tensor.2d.shared::cluster.global.mbarrier::complete_tx::bytes [%0], [%1, {%3, %4}], [%2];"
    :: "r"(dst), "l"(m), "r"(bar), "r"(c0), "r"(c1) : "memory");
}
__device__ __forceinline__ void tma3d(uint32_t dst, const CUtensorMap* m, int c0, int c1, int c2, uint32_t bar) {
  asm volatile("cp.async.bulk.tensor.3d.shared::cluster.global.mbarrier::complete_tx::bytes [%0], [%1, {%3, %4, %5}], [%2];"
    :: "r"(dst), "l"(m), "r"(bar), "r"(c0), "r"(c1), "r"(c2) : "memory");
}
__device__ __forceinline__ void tma5d(uint32_t dst, const CUtensorMap* m, int c0, int c4, uint32_t bar) {
  asm volatile("cp.async.bulk.tensor.5d.shared::cluster.global.mbarrier::complete_tx::bytes [%0], [%1, {%3, %5, %5, %5, %4}], [%2];"
    :: "r"(dst), "l"(m), "r"(bar), "r"(c0), "r"(c4), "r"(0) : "memory");
}
__device__ __forceinline__ void tma_pf2d(const CUtensorMap* m, int c0, int c1) {
  asm volatile("cp.async.bulk.prefetch.tensor.2d.L2.global [%0, {%1, %2}];" :: "l"(m), "r"(c0), "r"(c1) : "memory");
}
__device__ __forceinline__ void wg_fence() { asm volatile("wgmma.fence.sync.aligned;" ::: "memory"); }
__device__ __forceinline__ void wg_commit() { asm volatile("wgmma.commit_group.sync.aligned;" ::: "memory"); }
template <int N> __device__ __forceinline__ void wg_wait() { asm volatile("wgmma.wait_group.sync.aligned %0;" :: "n"(N) : "memory"); }
template <int N> __device__ __forceinline__ void reg_fence(float (&d)[N]) {
#pragma unroll
  for (int i = 0; i < N; i++) asm volatile("" : "+f"(d[i]) :: "memory");
}
__device__ __forceinline__ void wgmma4_n128_tb0(float (&d)[64], uint32_t a, uint32_t b, int scale_d) {
  asm volatile("{\n.reg .pred p;\n.reg .b32 la, lb, hi;\n.reg .b64 da, db;\nsetp.ne.b32 p, %66, 0;\nmov.b32 hi, 0x40000040;\n"
    "add.u32 la, %64, 0;\nadd.u32 lb, %65, 0;\nmov.b64 da, {la, hi};\nmov.b64 db, {lb, hi};\n"
    "wgmma.mma_async.sync.aligned.m64n128k16.f32.bf16.bf16 "
    "{%0, %1, %2, %3, %4, %5, %6, %7, %8, %9, %10, %11, %12, %13, %14, %15, %16, %17, %18, %19, %20, %21, %22, %23, %24, %25, %26, %27, %28, %29, %30, %31, %32, %33, %34, %35, %36, %37, %38, %39, %40, %41, %42, %43, %44, %45, %46, %47, %48, %49, %50, %51, %52, %53, %54, %55, %56, %57, %58, %59, %60, %61, %62, %63}, "
    "da, db, p, 1, 1, 0, 0;\n"
    "add.u32 la, %64, 2;\nadd.u32 lb, %65, 2;\nmov.b64 da, {la, hi};\nmov.b64 db, {lb, hi};\n"
    "wgmma.mma_async.sync.aligned.m64n128k16.f32.bf16.bf16 "
    "{%0, %1, %2, %3, %4, %5, %6, %7, %8, %9, %10, %11, %12, %13, %14, %15, %16, %17, %18, %19, %20, %21, %22, %23, %24, %25, %26, %27, %28, %29, %30, %31, %32, %33, %34, %35, %36, %37, %38, %39, %40, %41, %42, %43, %44, %45, %46, %47, %48, %49, %50, %51, %52, %53, %54, %55, %56, %57, %58, %59, %60, %61, %62, %63}, "
    "da, db, 1, 1, 1, 0, 0;\n"
    "add.u32 la, %64, 4;\nadd.u32 lb, %65, 4;\nmov.b64 da, {la, hi};\nmov.b64 db, {lb, hi};\n"
    "wgmma.mma_async.sync.aligned.m64n128k16.f32.bf16.bf16 "
    "{%0, %1, %2, %3, %4, %5, %6, %7, %8, %9, %10, %11, %12, %13, %14, %15, %16, %17, %18, %19, %20, %21, %22, %23, %24, %25, %26, %27, %28, %29, %30, %31, %32, %33, %34, %35, %36, %37, %38, %39, %40, %41, %42, %43, %44, %45, %46, %47, %48, %49, %50, %51, %52, %53, %54, %55, %56, %57, %58, %59, %60, %61, %62, %63}, "
    "da, db, 1, 1, 1, 0, 0;\n"
    "add.u32 la, %64, 6;\nadd.u32 lb, %65, 6;\nmov.b64 da, {la, hi};\nmov.b64 db, {lb, hi};\n"
    "wgmma.mma_async.sync.aligned.m64n128k16.f32.bf16.bf16 "
    "{%0, %1, %2, %3, %4, %5, %6, %7, %8, %9, %10, %11, %12, %13, %14, %15, %16, %17, %18, %19, %20, %21, %22, %23, %24, %25, %26, %27, %28, %29, %30, %31, %32, %33, %34, %35, %36, %37, %38, %39, %40, %41, %42, %43, %44, %45, %46, %47, %48, %49, %50, %51, %52, %53, %54, %55, %56, %57, %58, %59, %60, %61, %62, %63}, "
    "da, db, 1, 1, 1, 0, 0;\n"
    "}\n"
    : "+f"(d[0]), "+f"(d[1]), "+f"(d[2]), "+f"(d[3]), "+f"(d[4]), "+f"(d[5]), "+f"(d[6]), "+f"(d[7]), "+f"(d[8]), "+f"(d[9]), "+f"(d[10]), "+f"(d[11]), "+f"(d[12]), "+f"(d[13]), "+f"(d[14]), "+f"(d[15]), "+f"(d[16]), "+f"(d[17]), "+f"(d[18]), "+f"(d[19]), "+f"(d[20]), "+f"(d[21]), "+f"(d[22]), "+f"(d[23]), "+f"(d[24]), "+f"(d[25]), "+f"(d[26]), "+f"(d[27]), "+f"(d[28]), "+f"(d[29]), "+f"(d[30]), "+f"(d[31]), "+f"(d[32]), "+f"(d[33]), "+f"(d[34]), "+f"(d[35]), "+f"(d[36]), "+f"(d[37]), "+f"(d[38]), "+f"(d[39]), "+f"(d[40]), "+f"(d[41]), "+f"(d[42]), "+f"(d[43]), "+f"(d[44]), "+f"(d[45]), "+f"(d[46]), "+f"(d[47]), "+f"(d[48]), "+f"(d[49]), "+f"(d[50]), "+f"(d[51]), "+f"(d[52]), "+f"(d[53]), "+f"(d[54]), "+f"(d[55]), "+f"(d[56]), "+f"(d[57]), "+f"(d[58]), "+f"(d[59]), "+f"(d[60]), "+f"(d[61]), "+f"(d[62]), "+f"(d[63])
    : "r"(a), "r"(b), "r"(scale_d));
}
__device__ __forceinline__ void wgmma4_n128_tb1(float (&d)[64], uint32_t a, uint32_t b, int scale_d) {
  asm volatile("{\n.reg .pred p;\n.reg .b32 la, lb, hi;\n.reg .b64 da, db;\nsetp.ne.b32 p, %66, 0;\nmov.b32 hi, 0x40000040;\n"
    "add.u32 la, %64, 0;\nadd.u32 lb, %65, 0;\nmov.b64 da, {la, hi};\nmov.b64 db, {lb, hi};\n"
    "wgmma.mma_async.sync.aligned.m64n128k16.f32.bf16.bf16 "
    "{%0, %1, %2, %3, %4, %5, %6, %7, %8, %9, %10, %11, %12, %13, %14, %15, %16, %17, %18, %19, %20, %21, %22, %23, %24, %25, %26, %27, %28, %29, %30, %31, %32, %33, %34, %35, %36, %37, %38, %39, %40, %41, %42, %43, %44, %45, %46, %47, %48, %49, %50, %51, %52, %53, %54, %55, %56, %57, %58, %59, %60, %61, %62, %63}, "
    "da, db, p, 1, 1, 0, 1;\n"
    "add.u32 la, %64, 2;\nadd.u32 lb, %65, 128;\nmov.b64 da, {la, hi};\nmov.b64 db, {lb, hi};\n"
    "wgmma.mma_async.sync.aligned.m64n128k16.f32.bf16.bf16 "
    "{%0, %1, %2, %3, %4, %5, %6, %7, %8, %9, %10, %11, %12, %13, %14, %15, %16, %17, %18, %19, %20, %21, %22, %23, %24, %25, %26, %27, %28, %29, %30, %31, %32, %33, %34, %35, %36, %37, %38, %39, %40, %41, %42, %43, %44, %45, %46, %47, %48, %49, %50, %51, %52, %53, %54, %55, %56, %57, %58, %59, %60, %61, %62, %63}, "
    "da, db, 1, 1, 1, 0, 1;\n"
    "add.u32 la, %64, 4;\nadd.u32 lb, %65, 256;\nmov.b64 da, {la, hi};\nmov.b64 db, {lb, hi};\n"
    "wgmma.mma_async.sync.aligned.m64n128k16.f32.bf16.bf16 "
    "{%0, %1, %2, %3, %4, %5, %6, %7, %8, %9, %10, %11, %12, %13, %14, %15, %16, %17, %18, %19, %20, %21, %22, %23, %24, %25, %26, %27, %28, %29, %30, %31, %32, %33, %34, %35, %36, %37, %38, %39, %40, %41, %42, %43, %44, %45, %46, %47, %48, %49, %50, %51, %52, %53, %54, %55, %56, %57, %58, %59, %60, %61, %62, %63}, "
    "da, db, 1, 1, 1, 0, 1;\n"
    "add.u32 la, %64, 6;\nadd.u32 lb, %65, 384;\nmov.b64 da, {la, hi};\nmov.b64 db, {lb, hi};\n"
    "wgmma.mma_async.sync.aligned.m64n128k16.f32.bf16.bf16 "
    "{%0, %1, %2, %3, %4, %5, %6, %7, %8, %9, %10, %11, %12, %13, %14, %15, %16, %17, %18, %19, %20, %21, %22, %23, %24, %25, %26, %27, %28, %29, %30, %31, %32, %33, %34, %35, %36, %37, %38, %39, %40, %41, %42, %43, %44, %45, %46, %47, %48, %49, %50, %51, %52, %53, %54, %55, %56, %57, %58, %59, %60, %61, %62, %63}, "
    "da, db, 1, 1, 1, 0, 1;\n"
    "}\n"
    : "+f"(d[0]), "+f"(d[1]), "+f"(d[2]), "+f"(d[3]), "+f"(d[4]), "+f"(d[5]), "+f"(d[6]), "+f"(d[7]), "+f"(d[8]), "+f"(d[9]), "+f"(d[10]), "+f"(d[11]), "+f"(d[12]), "+f"(d[13]), "+f"(d[14]), "+f"(d[15]), "+f"(d[16]), "+f"(d[17]), "+f"(d[18]), "+f"(d[19]), "+f"(d[20]), "+f"(d[21]), "+f"(d[22]), "+f"(d[23]), "+f"(d[24]), "+f"(d[25]), "+f"(d[26]), "+f"(d[27]), "+f"(d[28]), "+f"(d[29]), "+f"(d[30]), "+f"(d[31]), "+f"(d[32]), "+f"(d[33]), "+f"(d[34]), "+f"(d[35]), "+f"(d[36]), "+f"(d[37]), "+f"(d[38]), "+f"(d[39]), "+f"(d[40]), "+f"(d[41]), "+f"(d[42]), "+f"(d[43]), "+f"(d[44]), "+f"(d[45]), "+f"(d[46]), "+f"(d[47]), "+f"(d[48]), "+f"(d[49]), "+f"(d[50]), "+f"(d[51]), "+f"(d[52]), "+f"(d[53]), "+f"(d[54]), "+f"(d[55]), "+f"(d[56]), "+f"(d[57]), "+f"(d[58]), "+f"(d[59]), "+f"(d[60]), "+f"(d[61]), "+f"(d[62]), "+f"(d[63])
    : "r"(a), "r"(b), "r"(scale_d));
}
__device__ __forceinline__ void wgmma4_n96_tb1(float (&d)[48], uint32_t a, uint32_t b, int scale_d) {
  asm volatile("{\n.reg .pred p;\n.reg .b32 la, lb, hi;\n.reg .b64 da, db;\nsetp.ne.b32 p, %50, 0;\nmov.b32 hi, 0x40000040;\n"
    "add.u32 la, %48, 0;\nadd.u32 lb, %49, 0;\nmov.b64 da, {la, hi};\nmov.b64 db, {lb, hi};\n"
    "wgmma.mma_async.sync.aligned.m64n96k16.f32.bf16.bf16 "
    "{%0, %1, %2, %3, %4, %5, %6, %7, %8, %9, %10, %11, %12, %13, %14, %15, %16, %17, %18, %19, %20, %21, %22, %23, %24, %25, %26, %27, %28, %29, %30, %31, %32, %33, %34, %35, %36, %37, %38, %39, %40, %41, %42, %43, %44, %45, %46, %47}, "
    "da, db, p, 1, 1, 0, 1;\n"
    "add.u32 la, %48, 2;\nadd.u32 lb, %49, 128;\nmov.b64 da, {la, hi};\nmov.b64 db, {lb, hi};\n"
    "wgmma.mma_async.sync.aligned.m64n96k16.f32.bf16.bf16 "
    "{%0, %1, %2, %3, %4, %5, %6, %7, %8, %9, %10, %11, %12, %13, %14, %15, %16, %17, %18, %19, %20, %21, %22, %23, %24, %25, %26, %27, %28, %29, %30, %31, %32, %33, %34, %35, %36, %37, %38, %39, %40, %41, %42, %43, %44, %45, %46, %47}, "
    "da, db, 1, 1, 1, 0, 1;\n"
    "add.u32 la, %48, 4;\nadd.u32 lb, %49, 256;\nmov.b64 da, {la, hi};\nmov.b64 db, {lb, hi};\n"
    "wgmma.mma_async.sync.aligned.m64n96k16.f32.bf16.bf16 "
    "{%0, %1, %2, %3, %4, %5, %6, %7, %8, %9, %10, %11, %12, %13, %14, %15, %16, %17, %18, %19, %20, %21, %22, %23, %24, %25, %26, %27, %28, %29, %30, %31, %32, %33, %34, %35, %36, %37, %38, %39, %40, %41, %42, %43, %44, %45, %46, %47}, "
    "da, db, 1, 1, 1, 0, 1;\n"
    "add.u32 la, %48, 6;\nadd.u32 lb, %49, 384;\nmov.b64 da, {la, hi};\nmov.b64 db, {lb, hi};\n"
    "wgmma.mma_async.sync.aligned.m64n96k16.f32.bf16.bf16 "
    "{%0, %1, %2, %3, %4, %5, %6, %7, %8, %9, %10, %11, %12, %13, %14, %15, %16, %17, %18, %19, %20, %21, %22, %23, %24, %25, %26, %27, %28, %29, %30, %31, %32, %33, %34, %35, %36, %37, %38, %39, %40, %41, %42, %43, %44, %45, %46, %47}, "
    "da, db, 1, 1, 1, 0, 1;\n"
    "}\n"
    : "+f"(d[0]), "+f"(d[1]), "+f"(d[2]), "+f"(d[3]), "+f"(d[4]), "+f"(d[5]), "+f"(d[6]), "+f"(d[7]), "+f"(d[8]), "+f"(d[9]), "+f"(d[10]), "+f"(d[11]), "+f"(d[12]), "+f"(d[13]), "+f"(d[14]), "+f"(d[15]), "+f"(d[16]), "+f"(d[17]), "+f"(d[18]), "+f"(d[19]), "+f"(d[20]), "+f"(d[21]), "+f"(d[22]), "+f"(d[23]), "+f"(d[24]), "+f"(d[25]), "+f"(d[26]), "+f"(d[27]), "+f"(d[28]), "+f"(d[29]), "+f"(d[30]), "+f"(d[31]), "+f"(d[32]), "+f"(d[33]), "+f"(d[34]), "+f"(d[35]), "+f"(d[36]), "+f"(d[37]), "+f"(d[38]), "+f"(d[39]), "+f"(d[40]), "+f"(d[41]), "+f"(d[42]), "+f"(d[43]), "+f"(d[44]), "+f"(d[45]), "+f"(d[46]), "+f"(d[47])
    : "r"(a), "r"(b), "r"(scale_d));
}

__device__ __forceinline__ void bar_arrive(int id, int n) { asm volatile("bar.arrive %0, %1;" :: "r"(id), "r"(n) : "memory"); }
__device__ __forceinline__ void bar_sync(int id, int n) { asm volatile("bar.sync %0, %1;" :: "r"(id), "r"(n) : "memory"); }
__device__ __forceinline__ unsigned ld_rlx(const unsigned* p) { unsigned v; asm volatile("ld.relaxed.gpu.global.u32 %0, [%1];" : "=r"(v) : "l"(p) : "memory"); return v; }
__device__ __forceinline__ void red_add(unsigned* p) { asm volatile("red.relaxed.gpu.global.add.u32 [%0], 1;" :: "l"(p) : "memory"); }
__device__ __forceinline__ void wait_cnt(const unsigned* p, unsigned target) {
  for (uint32_t n = 0; n < (1u << 14); n++) if ((int)(ld_rlx(p) - target) >= 0) break;
}
__device__ __forceinline__ float bf_lo(uint32_t v) { return __uint_as_float(v << 16); }
__device__ __forceinline__ float bf_hi(uint32_t v) { return __uint_as_float(v & 0xffff0000u); }
__device__ __forceinline__ uint32_t pack2(float lo, float hi) { uint32_t r; asm("cvt.rn.bf16x2.f32 %0, %1, %2;" : "=r"(r) : "f"(hi), "f"(lo)); return r; }
__device__ __forceinline__ uint32_t pack2v(float lo, float hi) { uint32_t r; asm volatile("cvt.rn.bf16x2.f32 %0, %1, %2;" : "=r"(r) : "f"(hi), "f"(lo)); return r; }
__device__ __forceinline__ float bfr(float v) { return __bfloat162float(__float2bfloat16_rn(v)); }
__device__ __forceinline__ uint32_t tagf(float v, uint32_t tag) { return (__float_as_uint(v) & ~3u) | tag; }
template <int OFF> __device__ __forceinline__ uint4 ld_msg(const void* p) { uint4 v; asm volatile("ld.relaxed.gpu.global.v4.u32 {%0,%1,%2,%3}, [%4 + %5];" : "=r"(v.x), "=r"(v.y), "=r"(v.z), "=r"(v.w) : "l"(p), "n"(OFF) : "memory"); return v; }
__device__ __forceinline__ void st_msg(void* p, uint32_t a, uint32_t b, uint32_t c, uint32_t d) { asm volatile("st.relaxed.gpu.global.v4.u32 [%0], {%1,%2,%3,%4};" :: "l"(p), "r"(a), "r"(b), "r"(c), "r"(d) : "memory"); }
__device__ __forceinline__ uint32_t stale(const uint4& v, uint32_t tag) { return ((v.x ^ tag) | (v.y ^ tag) | (v.z ^ tag) | (v.w ^ tag)) & 3u; }
__device__ __forceinline__ void sts4(uint32_t a, uint32_t x, uint32_t y, uint32_t z, uint32_t w) { asm volatile("st.shared.v4.u32 [%0], {%1,%2,%3,%4};" :: "r"(a), "r"(x), "r"(y), "r"(z), "r"(w) : "memory"); }
__device__ __forceinline__ void tma_st2d(const CUtensorMap* m, uint32_t src, int c0, int c1) {
  asm volatile("cp.async.bulk.tensor.2d.global.shared::cta.bulk_group [%0, {%2, %3}], [%1];" :: "l"(m), "r"(src), "r"(c0), "r"(c1) : "memory");
}
__device__ __forceinline__ void tma_st3d(const CUtensorMap* m, uint32_t src, int c0, int c1, int c2) {
  asm volatile("cp.async.bulk.tensor.3d.global.shared::cta.bulk_group [%0, {%2, %3, %4}], [%1];" :: "l"(m), "r"(src), "r"(c0), "r"(c1), "r"(c2) : "memory");
}
__device__ __forceinline__ float rcp_f(float v) { float r; asm("rcp.approx.f32 %0, %1;" : "=f"(r) : "f"(v)); return r; }
__device__ __forceinline__ float sqrt_f(float v) { float r; asm("sqrt.approx.f32 %0, %1;" : "=f"(r) : "f"(v)); return r; }
__device__ __forceinline__ float tanh_f(float v) { float r; asm("tanh.approx.f32 %0, %1;" : "=f"(r) : "f"(v)); return r; }
__device__ __forceinline__ float gelu_half(float hf) {
  const float k0 = 2.0f * 0.7978845608028654f, k1 = 8.0f * 0.7978845608028654f * 0.044715f;
  return fmaf(hf, tanh_f(hf * fmaf(hf * hf, k1, k0)), hf);
}
__device__ __forceinline__ uint2 ld_msg2(const void* p) { uint2 v; asm volatile("ld.relaxed.gpu.global.v2.u32 {%0,%1}, [%2];" : "=r"(v.x), "=r"(v.y) : "l"(p) : "memory"); return v; }
__device__ __forceinline__ void fence_async_smem() { asm volatile("fence.proxy.async.shared::cta;" ::: "memory"); }
template <int OFF> __device__ __forceinline__ uint4 ldg_nc(const void* p) { uint4 v; asm volatile("ld.global.nc.v4.u32 {%0,%1,%2,%3}, [%4 + %5];" : "=r"(v.x), "=r"(v.y), "=r"(v.z), "=r"(v.w) : "l"(p), "n"(OFF)); return v; }
__device__ __forceinline__ void stg4(void* p, uint32_t a, uint32_t b, uint32_t c, uint32_t d) { asm volatile("st.global.v4.u32 [%0], {%1,%2,%3,%4};" :: "l"(p), "r"(a), "r"(b), "r"(c), "r"(d) : "memory"); }
__device__ __forceinline__ float4 lds4f(uint32_t a) { float4 v; asm volatile("ld.shared.v4.f32 {%0,%1,%2,%3}, [%4];" : "=f"(v.x), "=f"(v.y), "=f"(v.z), "=f"(v.w) : "r"(a)); return v; }
__device__ __forceinline__ uint4 lds4u(uint32_t a) { uint4 v; asm volatile("ld.shared.v4.u32 {%0,%1,%2,%3}, [%4];" : "=r"(v.x), "=r"(v.y), "=r"(v.z), "=r"(v.w) : "r"(a) : "memory"); return v; }
__device__ __forceinline__ float2 lds2f(uint32_t a) { float2 v; asm volatile("ld.shared.v2.f32 {%0,%1}, [%2];" : "=f"(v.x), "=f"(v.y) : "r"(a)); return v; }
__device__ __forceinline__ void st_async4(uint32_t raddr, uint32_t a, uint32_t b, uint32_t c, uint32_t d, uint32_t rbar) {
  asm volatile("st.async.weak.shared::cluster.mbarrier::complete_tx::bytes.v4.b32 [%0], {%1,%2,%3,%4}, [%5];"
    :: "r"(raddr), "r"(a), "r"(b), "r"(c), "r"(d), "r"(rbar) : "memory");
}

struct Ctx {
  uint32_t sm;
  uint32_t da;
  uint32_t db;
  bool lead;
};
template <int V> struct IC { static constexpr int value = V; };
template <int S0, int S1, class F>
__device__ __forceinline__ void static_for(F&& f) {
  if constexpr (S0 < S1) { f(IC<S0>{}); static_for<S0 + 1, S1>(f); }
}
template <int N, int TB>
__device__ __forceinline__ void mma_issue(float (&acc)[N / 2], const Ctx& c, uint32_t offa, uint32_t offb, int accum) {
  const uint32_t a = c.da + (offa >> 4), b = c.db + (offb >> 4) + (TB ? (512u << 16) : (1u << 16));
  wg_fence();
  if constexpr (N == 128 && TB == 0) wgmma4_n128_tb0(acc, a, b, accum);
  if constexpr (N == 128 && TB == 1) wgmma4_n128_tb1(acc, a, b, accum);
  if constexpr (N == 96) wgmma4_n96_tb1(acc, a, b, accum);
  wg_commit();
}
template <int N, int S>
__device__ __forceinline__ void step1(float (&acc)[N / 2], const Ctx& c) {
  if (S < 8) mbar_wait(c.sm + OFF_BAR + BAR_XF + 8 * S, 0);
  mbar_wait(c.sm + OFF_BAR + BAR_BF + 8 * (S & 3), (S >> 2) & 1);
  mma_issue<N, 1>(acc, c, xslot(S & 7), bslot(S & 3), (S & 7) != 0);
}
template <int TB>
__device__ __forceinline__ void step2(float (&acc)[64], const Ctx& c, int st, uint32_t ph, int accum) {
  mbar_wait(c.sm + OFF_BAR + BAR_FULL + 8 * st, ph);
  mma_issue<128, TB>(acc, c, st * STB, st * STB + 16384, accum);
}
__device__ __forceinline__ void release2(const Ctx& c, int st) {
  if (c.lead) mbar_arrive(c.sm + OFF_BAR + BAR_EMPTY + 8 * st);
}
template <int S>
__device__ __forceinline__ void release(const Ctx& c) {
  if constexpr (S < S_S) {
    if (c.lead) {
      if constexpr (S < 12) mbar_arrive(c.sm + OFF_BAR + BAR_BE + 8 * (S & 3));
      if constexpr (S == 9) mbar_arrive(c.sm + OFF_BAR + BAR_EMPTY);
      if constexpr (S >= 11) mbar_arrive(c.sm + OFF_BAR + BAR_EMPTY + 8 * (S - 10));
    }
  } else if constexpr (S < S_END - NST) {
    release2(c, stage_of(S));
  }
}

struct HEpi { float a0, b0, a1, b1; uint32_t vec, stg, never; uint32_t w0[4], w1[4]; };
template <int G, int I, int VG, int NA>
__device__ __forceinline__ void h_unit(const float (&acc)[NA], HEpi& e) {
  const float4 v = lds4f(e.vec + (16 * VG + 4 * I) * 16);
  const int r = 4 * (4 * G + I);
  e.w0[I] = pack2v(gelu_half(fmaf(e.a0, acc[r], fmaf(e.b0, v.x, v.z))), gelu_half(fmaf(e.a0, acc[r + 1], fmaf(e.b0, v.y, v.w))));
  e.w1[I] = pack2v(gelu_half(fmaf(e.a1, acc[r + 2], fmaf(e.b1, v.x, v.z))), gelu_half(fmaf(e.a1, acc[r + 3], fmaf(e.b1, v.y, v.w))));
  if (I < 3)
    asm volatile("{\n.reg .pred p;\nsetp.ne.u32 p, %0, 0;\n@p st.shared.v2.u32 [%1], {%2, %3};\n}" :: "r"(e.never), "r"(e.stg), "r"(e.w0[I]), "r"(e.w1[I]) : "memory");
  if (I == 3) {
    sts4(e.stg + G * 8192, e.w0[0], e.w0[1], e.w0[2], e.w0[3]);
    sts4(e.stg + G * 8192 + 512, e.w1[0], e.w1[1], e.w1[2], e.w1[3]);
  }
}

__global__ void __cluster_dims__(2, 1, 1) __launch_bounds__(384, 1) fused_kernel(const __grid_constant__ Params p) {
  extern __shared__ __align__(1024) uint8_t smem_raw[];
  const uint32_t sm = (uint32_t)__cvta_generic_to_shared(smem_raw);
  const int tid = threadIdx.x, lane = tid & 31;
  const int warp = __shfl_sync(0xffffffffu, tid >> 5, 0);
  int lc;
  {
    const int c = blockIdx.x >> 1;
    if (c < 4) lc = 4 + c;
    else if (c < 36) lc = ((c - 4) & 7) * 8 + ((c - 4) >> 3);
    else lc = (1 + (c - 36) % 7) * 8 + 4 + (c - 36) / 7;
  }
  const int rk = blockIdx.x & 1, cb = lc & 3, rb = lc >> 2, j = cb * 2 + rk;
  const int row0 = rb * 128;
  const uint32_t bars = sm + OFF_BAR;
  TLC(0);
#define EPOCH() mbar_wait(bars + BAR_E, 0); unsigned epoch; asm volatile("ld.shared.u32 %0, [%1];" : "=r"(epoch) : "r"(bars + OFF_EPOCH) : "memory"); const uint32_t tag = epoch & 3
  if (warp >= 8) {
    asm volatile("setmaxnreg.dec.sync.aligned.u32 88;");
    if (warp == 8) {
      if (elect_one()) {
        for (int s = 0; s < 8; s++) mbar_init(bars + BAR_XF + 8 * s, 1);
        for (int s = 0; s < 4; s++) { mbar_init(bars + BAR_BF + 8 * s, 1); mbar_init(bars + BAR_BE + 8 * s, 8); }
        mbar_init(bars + BAR_X16, 1);
        fence_async_smem();
        for (int k = 0; k < 8; k++) {
          mbar_expect_tx(bars + BAR_XF + 8 * k, 16384);
          tma2d(sm + xslot(k), &p.mx, k * 64, row0, bars + BAR_XF + 8 * k);
          if (k < 4) {
            mbar_expect_tx(bars + BAR_BF + 8 * k, 16384);
            tma3d(sm + bslot(k), &p.mw1, j * 224 + 96, k * 64, 0, bars + BAR_BF + 8 * k);
          }
          if (k == X16_AT) {
            mbar_expect_tx(bars + BAR_X16, 16384);
            tma2d(sm + OFF_STG, &p.mx16, 0, (row0 + j * 16) * 8, bars + BAR_X16);
          }
        }
        for (int s = 0; s < NST; s++) { mbar_init(bars + BAR_FULL + 8 * s, 1); mbar_init(bars + BAR_EMPTY + 8 * s, 8); }
        mbar_init(bars + BAR_V, 2); mbar_init(bars + BAR_FREE, 1); mbar_init(bars + BAR_E, 1); mbar_init(bars + BAR_DEP, 1);
        mbar_init(bars + BAR_M, 1); mbar_init(bars + BAR_Y, 1); mbar_init(bars + BAR_OK, 8);
        asm volatile("fence.mbarrier_init.release.cluster;" ::: "memory");
        fence_async_smem();
        mbar_expect_tx(bars + BAR_M, 16384);
        mbar_expect_tx(bars + BAR_Y, 16384);
      }
      __syncwarp();
      __syncthreads();
      asm volatile("barrier.cluster.arrive.relaxed.aligned;" ::: "memory");
      if (elect_one()) {
        const CUtensorMap* mc = rk ? &p.mci : &p.mcr;
        const CUtensorMap* md = rk ? &p.mdim : &p.mdre;
        asm volatile("prefetch.tensormap [%0];" :: "l"(mc) : "memory");
        asm volatile("prefetch.tensormap [%0];" :: "l"(&p.mxn) : "memory");
        asm volatile("prefetch.tensormap [%0];" :: "l"(&p.mh) : "memory");
        asm volatile("prefetch.tensormap [%0];" :: "l"(&p.mw2) : "memory");
        asm volatile("prefetch.tensormap [%0];" :: "l"(&p.muv) : "memory");
        asm volatile("prefetch.tensormap [%0];" :: "l"(md) : "memory");
        for (int k = 4; k < 16; k++) {
          const uint32_t fb = bars + BAR_BF + 8 * (k & 3);
          mbar_wait(bars + BAR_BE + 8 * (k & 3), ((k >> 2) & 1) ^ 1);
          mbar_expect_tx(fb, 16384);
          tma3d(sm + bslot(k & 3), &p.mw1, j * 224 + (k < 8 ? 96 : 0), (k & 7) * 64, 0, fb);
          if (k == 9) tma_pf2d(mc, cb * 64, row0);
        }
        int st = 0; uint32_t ph = 0;
#define P_ACQ() mbar_wait(bars + BAR_EMPTY + 8 * st, ph); const uint32_t fb = bars + BAR_FULL + 8 * st, sa = sm + st * STB, sb = sa + 16384; mbar_expect_tx(fb, STB)
#define P_ADV() if (++st == NST) { st = 0; ph ^= 1; }
        TLREC(11);
        mbar_wait(bars + BAR_DEP, 0);
        asm volatile("fence.proxy.async.global;" ::: "memory");
        TLREC(12);
        for (int k = 0; k < 32; k++) {
          P_ACQ(); tma2d(sa, mc, k * 64, row0, fb); tma3d(sb, &p.mxn, 0, k * 64, cb * 2, fb); P_ADV();
        }
        TLREC(13);
        mbar_wait(bars + BAR_DEP, 1);
        asm volatile("fence.proxy.async.global;" ::: "memory");
        TLREC(14);
        const int n0 = cb * 128 + rk * 64, n1 = cb * 128 + (rk ^ 1) * 64;
        for (int k = rk * 14; k < rk * 14 + 14; k++) {
          P_ACQ(); tma2d(sa, &p.mh, k * 64, row0, fb); tma5d(sb, &p.mw2, n0, 2 * k, fb); tma5d(sb + 8192, &p.mw2, n1, 2 * k, fb); P_ADV();
        }
        TLREC(22);
        mbar_wait(bars + BAR_DEP, 0);
        asm volatile("fence.proxy.async.global;" ::: "memory");
        TLREC(23);
        red_add(&g_cnt[C_DONE]);
#pragma unroll 1
        for (int k = 0; k < 8; k++) {
          P_ACQ(); tma2d(sa, &p.muv, k * 64, rk * SEQ + row0, fb); tma5d(sb, md, k * 64, n0 >> 5, fb); tma5d(sb + 8192, md, k * 64, n1 >> 5, fb); P_ADV();
        }
      }
    } else if (warp == 9) {
      unsigned done0 = 0;
      if (lane == 0) done0 = ld_rlx(&g_cnt[C_DONE]);
      __syncthreads();
      asm volatile("barrier.cluster.arrive.relaxed.aligned;" ::: "memory");
      const unsigned epoch = (done0 >> 7) + 1;
      if (lane == 0) {
        asm volatile("st.shared.u32 [%0], %1;" :: "r"(bars + OFF_EPOCH), "r"(epoch) : "memory");
        mbar_arrive(bars + BAR_E);
        asm volatile("prefetch.tensormap [%0];" :: "l"(&p.sxn) : "memory");
        asm volatile("prefetch.tensormap [%0];" :: "l"(&p.sh) : "memory");
        asm volatile("prefetch.tensormap [%0];" :: "l"(&p.suv) : "memory");
      }
#pragma unroll 1
      for (int tile = 0; tile < 4; tile++) {
        bar_sync(1 + tile, 288);
        if (lane == 0) {
          TLREC(24 + tile);
          unsigned* cnt = &g_cnt[tile == 0 ? C_XN : (tile == 3 ? C_UV : C_H) + rb * 32];
          if (tile == 0) {
            tma_st2d(&p.sxn, sm + OFF_STG, 0, (row0 + j * 16) * 8);
          } else {
            const CUtensorMap* m = tile == 3 ? &p.suv : &p.sh;
            const int c0 = tile == 3 ? cb * 128 : j * 224 + (tile == 1 ? 96 : 0), r0 = (tile == 3 ? rk * SEQ : 0) + row0;
#pragma unroll 1
            for (int g = 0; g < (tile == 2 ? 3 : 4); g++) tma_st2d(m, sm + OFF_STG + g * 8192, c0 + g * 32, r0);
          }
          asm volatile("cp.async.bulk.commit_group;\ncp.async.bulk.wait_group.read 0;" ::: "memory");
          mbar_arrive(bars + BAR_FREE);
          asm volatile("cp.async.bulk.wait_group 0;" ::: "memory");
          red_add(cnt);
          TLREC(16 + tile);
          if (tile != 1) { wait_cnt(cnt, (tile == 0 ? 128 : tile == 2 ? 16 : 8) * epoch); mbar_arrive(bars + BAR_DEP); }
        }
        __syncwarp();
      }
    } else {
      const int cl = lane < 28 ? lane : 27;
      const __nv_bfloat16* w = p.w1 + (size_t)(rb * 32 + (warp - 10) * 16) * FF + j * 224 + cl * 8;
      __syncthreads();
      asm volatile("barrier.cluster.arrive.relaxed.aligned;" ::: "memory");
      {
        uint4 v[16];
        static_for<0, 16>([&](auto I) { v[decltype(I)::value] = ldg_nc<decltype(I)::value * FF * 2>(w); });
        float s[8] = {0.f, 0.f, 0.f, 0.f, 0.f, 0.f, 0.f, 0.f};
#pragma unroll
        for (int r = 0; r < 16; r++) {
          s[0] += bf_lo(v[r].x); s[1] += bf_hi(v[r].x); s[2] += bf_lo(v[r].y); s[3] += bf_hi(v[r].y);
          s[4] += bf_lo(v[r].z); s[5] += bf_hi(v[r].z); s[6] += bf_lo(v[r].w); s[7] += bf_hi(v[r].w);
        }
        float4* s4 = reinterpret_cast<float4*>(smem_raw + OFF_VH);
        if (warp == 11 && lane < 28) { s4[lane * 2] = make_float4(s[0], s[1], s[2], s[3]); s4[lane * 2 + 1] = make_float4(s[4], s[5], s[6], s[7]); }
        bar_sync(5, 64);
        EPOCH();
        if (warp == 10 && lane < 28) {
          const float4 o0 = s4[lane * 2], o1 = s4[lane * 2 + 1];
          float* dst = &g_csw[rb * FF + j * 224 + lane * 8];
          st_msg(dst, tagf(s[0] + o0.x, tag), tagf(s[1] + o0.y, tag), tagf(s[2] + o0.z, tag), tagf(s[3] + o0.w, tag));
          st_msg(dst + 4, tagf(s[4] + o1.x, tag), tagf(s[5] + o1.y, tag), tagf(s[6] + o1.z, tag), tagf(s[7] + o1.w, tag));
          if (lane == 0) TLREC(15);
        }
        bar_sync(5, 64);
      }
      EPOCH();
      const int q = (warp - 10) * 28 + cl;
      const uint2 bb = *reinterpret_cast<const uint2*>(p.b1 + j * 224 + q * 4);
      if (warp == 11) {
        const uint32_t b2v = *reinterpret_cast<const uint32_t*>(p.b2 + cb * 128 + rk * 64 + lane * 2);
        *reinterpret_cast<float2*>(smem_raw + OFF_B2 + lane * 8) = make_float2(0.5f * bf_lo(b2v), 0.5f * bf_hi(b2v));
      }
      float4 acc;
      for (uint32_t n = 0; n < (1u << 14); n++) {
        uint32_t bad = 0;
        acc = make_float4(0.f, 0.f, 0.f, 0.f);
        uint4 m[16];
        static_for<0, 16>([&](auto I) { m[decltype(I)::value] = ld_msg<decltype(I)::value * FF * 4>(&g_csw[j * 224 + q * 4]); });
#pragma unroll
        for (int r = 0; r < 16; r++) {
          bad |= stale(m[r], tag);
          acc.x += __uint_as_float(m[r].x); acc.y += __uint_as_float(m[r].y); acc.z += __uint_as_float(m[r].z); acc.w += __uint_as_float(m[r].w);
        }
        if (!__any_sync(0xffffffffu, bad)) break;
      }
      if (lane < 28) {
        float4* s4 = reinterpret_cast<float4*>(smem_raw + OFF_VH);
        s4[q * 2] = make_float4(acc.x, acc.y, 0.5f * bf_lo(bb.x), 0.5f * bf_hi(bb.x));
        s4[q * 2 + 1] = make_float4(acc.z, acc.w, 0.5f * bf_lo(bb.y), 0.5f * bf_hi(bb.y));
      }
      __syncwarp();
      if (lane == 0) { mbar_arrive(bars + BAR_V); if (warp == 10) TLREC(20); }
    }
  } else {
    asm volatile("setmaxnreg.inc.sync.aligned.u32 208;");
    __syncthreads();
    asm volatile("barrier.cluster.arrive.relaxed.aligned;" ::: "memory");
    Ctx c; c.sm = sm; c.lead = lane == 0;
    c.da = (((sm + (warp >> 2) * 8192) & 0x3FFFF) >> 4) | (1u << 16); c.db = (sm & 0x3FFFF) >> 4;
    const int rl = warp * 16 + (lane >> 2);
    float Q[64], R[48], U[64], M[64], Y[64];
    HEpi e;
    e.vec = sm + OFF_VH + (lane & 3) * 16; e.stg = sm + OFF_STG + rl * 64 + (lane & 3) * 16;
    e.never = gridDim.y - 1;
    uint2 m0, m1;
    uint32_t xw[4][4];
    float mu[2], qq[2];
    static_for<0, S_ROLL>([&](auto S_) {
      constexpr int S = decltype(S_)::value;
      if constexpr (S < 8) step1<128, S>(Q, c);
      else if constexpr (S < S_S) step1<96, S>(R, c);
      else step2<1>(U, c, stage_of(S), par_of(S), S > S_S);
      if (S == 0) TLC(1);
      if (S == HS0 - 1) { m0 = ld_msg2(&g_stats[row0 + rl]); m1 = ld_msg2(&g_stats[row0 + rl + 8]); }
      if constexpr (S > 0) { wg_wait<1>(); release<S - 1>(c); }
      if (S == XS0) {
        mbar_wait(bars + BAR_X16, 0);
#pragma unroll
        for (int t = 0; t < 4; t++) {
          const int kc = (t & 1) * 4 + (lane >> 3);
          const uint4 v = lds4u(sm + OFF_STG + (warp * 2 + (t >> 1)) * 1024 + kc * 128 + (((lane & 7) ^ kc) << 4));
          xw[t][0] = v.x; xw[t][1] = v.y; xw[t][2] = v.z; xw[t][3] = v.w;
        }
#pragma unroll
        for (int r = 0; r < 2; r++) {
          float a = 0.f, b = 0.f;
#pragma unroll
          for (int i = 0; i < 8; i++) { a += bf_lo(xw[2 * r + (i >> 2)][i & 3]); b += bf_hi(xw[2 * r + (i >> 2)][i & 3]); }
          mu[r] = a + b;
        }
#pragma unroll
        for (int o = 16; o > 0; o >>= 1) { mu[0] += __shfl_xor_sync(0xffffffffu, mu[0], o); mu[1] += __shfl_xor_sync(0xffffffffu, mu[1], o); }
      }
      if (S == XS0 + 1) {
#pragma unroll
        for (int r = 0; r < 2; r++) {
          mu[r] *= 1.0f / DM;
          const uint32_t mm = pack2(mu[r], mu[r]);
          float a = 0.f, b = 0.f;
#pragma unroll
          for (int i = 0; i < 8; i++) {
            uint32_t& w = xw[2 * r + (i >> 2)][i & 3];
            asm("sub.rn.bf16x2 %0, %0, %1;" : "+r"(w) : "r"(mm));
            a = fmaf(bf_lo(w), bf_lo(w), a); b = fmaf(bf_hi(w), bf_hi(w), b);
          }
          qq[r] = a + b;
        }
#pragma unroll
        for (int o = 16; o > 0; o >>= 1) { qq[0] += __shfl_xor_sync(0xffffffffu, qq[0], o); qq[1] += __shfl_xor_sync(0xffffffffu, qq[1], o); }
      }
      if (S == XS0 + 2) {
        const float mean = (lane & 1) ? mu[1] : mu[0], m1 = bfr(mean), dm = mean - m1;
        const float var = fmaxf(fmaf((lane & 1) ? qq[1] : qq[0], 1.0f / DM, -dm * dm), 0.f);
        const float i1 = rcp_f(bfr(sqrt_f(bfr(bfr(var) + 1e-5f))));
        const float i2 = 0.5f * rcp_f(bfr(sqrt_f(bfr(bfr(var * i1 * i1) + 1e-5f))));
        const float rh = bfr(i1);
        const uint32_t hl = pack2(rh, i1 - rh);
        EPOCH();
        if (lane < 2)
          asm volatile("st.relaxed.gpu.global.v2.u32 [%0], {%1,%2};" :: "l"(&g_stats[row0 + j * 16 + warp * 2 + lane]), "r"(tagf(i1 * i2, tag)), "r"(tagf(-(m1 * i1 + bfr(dm * i1)) * i2, tag)) : "memory");
#pragma unroll
        for (int r = 0; r < 2; r++) {
          const uint32_t t = __shfl_sync(0xffffffffu, hl, r), hi = __byte_perm(t, 0, 0x1010), lo = __byte_perm(t, 0, 0x3232);
#pragma unroll
          for (int i = 0; i < 8; i++) {
            uint32_t& w = xw[2 * r + (i >> 2)][i & 3];
            asm("{\n.reg .b32 t;\nmul.rn.bf16x2 t, %0, %2;\nfma.rn.bf16x2 %0, %0, %1, t;\n}" : "+r"(w) : "r"(hi), "r"(lo));
          }
        }
#pragma unroll
        for (int t = 0; t < 4; t++) {
          const int kc = (t & 1) * 4 + ((lane & 7) >> 1);
          asm volatile("stmatrix.sync.aligned.m8n8.x4.shared.b16 [%0], {%1,%2,%3,%4};"
                       :: "r"(sm + OFF_STG + (warp * 2 + (t >> 1)) * 1024 + kc * 128 + ((((lane & 1) * 4 + (lane >> 3)) ^ kc) << 4)),
                          "r"(xw[t][0]), "r"(xw[t][1]), "r"(xw[t][2]), "r"(xw[t][3]) : "memory");
        }
        fence_async_smem();
        bar_arrive(1, 288);
        TLC(28);
      }
      if (S == 8) { reg_fence(Q); TLC(2); }
      if (S == S_S) { reg_fence(R); TLC(3); }
      if (S == HS0) {
        EPOCH();
        for (uint32_t n = 0; n < (1u << 14) && (((m0.x ^ tag) | (m0.y ^ tag) | (m1.x ^ tag) | (m1.y ^ tag)) & 3u); n++) {
          m0 = ld_msg2(&g_stats[row0 + rl]); m1 = ld_msg2(&g_stats[row0 + rl + 8]);
        }
        e.a0 = __uint_as_float(m0.x); e.b0 = __uint_as_float(m0.y); e.a1 = __uint_as_float(m1.x); e.b1 = __uint_as_float(m1.y);
        mbar_wait(bars + BAR_V, 0);
        TLC(21);
      }
      static_for<units_done(S - 1), units_done(S)>([&](auto U_) {
        constexpr int u = decltype(U_)::value;
        if (u == 3) mbar_wait(bars + BAR_FREE, 0);
        if (u == 19) mbar_wait(bars + BAR_FREE, 1);
        if constexpr (u < 16) h_unit<u / 4, u % 4, 3 + u / 4>(Q, e);
        else h_unit<(u - 16) / 4, u % 4, (u - 16) / 4>(R, e);
        if (u == 15 || u == 27) { fence_async_smem(); bar_arrive(u == 15 ? 2 : 3, 288); }
      });
    });
    TLC(4);
    int st = stage_of(S_ROLL), pst = stage_of(S_ROLL - 1); uint32_t ph = par_of(S_ROLL);
#pragma unroll 1
    for (int s = S_ROLL; s < S_M; s++) {
      step2<1>(U, c, st, ph, 1);
      wg_wait<1>();
      release2(c, pst);
      pst = st; if (++st == NST) { st = 0; ph ^= 1; }
    }
    TLC(5);
    step2<1>(M, c, stage_of(S_M), par_of(S_M), 0);
    wg_wait<1>();
    release<S_M - 1>(c);
    reg_fence(U);
    mbar_wait(bars + BAR_FREE, 0);
#pragma unroll
    for (int G = 0; G < 4; G++) {
      const int r = 16 * G;
      sts4(e.stg + G * 8192, pack2(U[r], U[r + 1]), pack2(U[r + 4], U[r + 5]), pack2(U[r + 8], U[r + 9]), pack2(U[r + 12], U[r + 13]));
      sts4(e.stg + G * 8192 + 512, pack2(U[r + 2], U[r + 3]), pack2(U[r + 6], U[r + 7]), pack2(U[r + 10], U[r + 11]), pack2(U[r + 14], U[r + 15]));
    }
    fence_async_smem();
    bar_arrive(4, 288);
    st = stage_of(S_M + 1); pst = stage_of(S_M); ph = par_of(S_M + 1);
#pragma unroll 1
    for (int s = S_M + 1; s < S_Y; s++) {
      step2<1>(M, c, st, ph, 1);
      wg_wait<1>();
      release2(c, pst);
      pst = st; if (++st == NST) { st = 0; ph ^= 1; }
    }
    TLC(6);
    const size_t ooff = (size_t)(row0 + rl) * DM + cb * 128 + rk * 64 + (lane & 3) * 8;
    const uint32_t mine = warp * 4096 + lane * 16, peer = rk ^ 1, sgn = rk ? 0x80008000u : 0u;
    uint4 g[4], xr[4];
    static_for<S_Y, S_END>([&](auto S_) {
      constexpr int S = decltype(S_)::value;
      step2<0>(Y, c, stage_of(S), par_of(S), S > S_Y);
      wg_wait<1>();
      release<S - 1>(c);
      if (S == S_Y) {
        reg_fence(M);
        asm volatile("barrier.cluster.wait.aligned;" ::: "memory");
        const uint32_t ra = mapa(sm + OFF_STG + mine, peer), rbar = mapa(bars + BAR_M, peer);
#pragma unroll
        for (int v = 0; v < 4; v++)
          st_async4(ra + v * 512, pack2(M[32 + 8 * v], M[33 + 8 * v]), pack2(M[34 + 8 * v], M[35 + 8 * v]), pack2(M[36 + 8 * v], M[37 + 8 * v]), pack2(M[38 + 8 * v], M[39 + 8 * v]), rbar);
        xr[0] = ldg_nc<0>(p.x + ooff); xr[1] = ldg_nc<16 * DM>(p.x + ooff);
        xr[2] = ldg_nc<64>(p.x + ooff); xr[3] = ldg_nc<16 * DM + 64>(p.x + ooff);
      }
      if (S == S_Y + 3) {
        mbar_wait(bars + BAR_M, 0);
#pragma unroll
        for (int v = 0; v < 4; v++) {
          const uint4 t = lds4u(sm + OFF_STG + mine + v * 512);
          M[8 * v] += bf_lo(t.x); M[8 * v + 1] += bf_hi(t.x); M[8 * v + 2] += bf_lo(t.y); M[8 * v + 3] += bf_hi(t.y);
          M[8 * v + 4] += bf_lo(t.z); M[8 * v + 5] += bf_hi(t.z); M[8 * v + 6] += bf_lo(t.w); M[8 * v + 7] += bf_hi(t.w);
        }
      }
      if (S == S_END - NST + 1 && c.lead) mbar_arrive_cluster(mapa(bars + BAR_OK, peer));
      if constexpr (S >= S_Y + 4) {
        constexpr int G = (S - S_Y - 4) >> 1, H = (S - S_Y - 4) & 1;
        uint32_t w[4];
#pragma unroll
        for (int i = 0; i < 4; i++) {
          const float2 b = lds2f(sm + OFF_B2 + (32 * G + 8 * i) * 4 + (lane & 3) * 8);
          const int r = 4 * (4 * G + i) + 2 * H;
          const float z0 = fmaf(M[r], 0.5f, b.x), z1 = fmaf(M[r + 1], 0.5f, b.y);
          w[i] = pack2(fmaf(z0, tanh_f(z0), z0), fmaf(z1, tanh_f(z1), z1)) ^ sgn;
        }
        const uint32_t tb = sm + OFF_STG + warp * 4096 + (2 * G + H) * 512;
        __syncwarp();
        asm volatile("stmatrix.sync.aligned.m8n8.x4.shared.b16 [%0], {%1,%2,%3,%4};"
                     :: "r"(tb + (lane & 7) * 64 + (((lane >> 3) ^ ((lane >> 1) & 3)) << 4)), "r"(w[0]), "r"(w[1]), "r"(w[2]), "r"(w[3]) : "memory");
        __syncwarp();
        g[2 * G + H] = lds4u(tb + (lane >> 2) * 64 + (((lane & 3) ^ ((lane >> 3) & 3)) << 4));
      }
    });
    mbar_wait(bars + BAR_OK, 0);
    const uint32_t rl_ = mapa(sm + LAND_STAGE * STB + mine, peer), rlb = mapa(bars + BAR_Y, peer);
    TLC(7);
    wg_wait<0>();
    reg_fence(Y);
    TLC(8);
#pragma unroll
    for (int v = 0; v < 4; v++)
      st_async4(rl_ + v * 512, pack2(Y[32 + 8 * v], Y[33 + 8 * v]), pack2(Y[34 + 8 * v], Y[35 + 8 * v]), pack2(Y[36 + 8 * v], Y[37 + 8 * v]), pack2(Y[38 + 8 * v], Y[39 + 8 * v]), rlb);
    mbar_wait(bars + BAR_Y, 0);
    TLC(9);
#pragma unroll
    for (int G = 0; G < 2; G++) {
      uint32_t o0[4], o1[4];
      const uint4 tv[2] = {lds4u(sm + LAND_STAGE * STB + mine + 2 * G * 512), lds4u(sm + LAND_STAGE * STB + mine + (2 * G + 1) * 512)};
      const uint32_t g0[4] = {g[2 * G].x, g[2 * G].y, g[2 * G].z, g[2 * G].w}, g1[4] = {g[2 * G + 1].x, g[2 * G + 1].y, g[2 * G + 1].z, g[2 * G + 1].w};
      const uint32_t x0[4] = {xr[2 * G].x, xr[2 * G].y, xr[2 * G].z, xr[2 * G].w}, x1[4] = {xr[2 * G + 1].x, xr[2 * G + 1].y, xr[2 * G + 1].z, xr[2 * G + 1].w};
#pragma unroll
      for (int i = 0; i < 4; i++) {
        const int a = 4 * (4 * G + i);
        const uint32_t t0 = (i & 1) ? tv[i >> 1].z : tv[i >> 1].x, t1 = (i & 1) ? tv[i >> 1].w : tv[i >> 1].y;
        o0[i] = pack2(fmaf(Y[a] - bf_lo(t0), bf_lo(g0[i]), bf_lo(x0[i])), fmaf(Y[a + 1] - bf_hi(t0), bf_hi(g0[i]), bf_hi(x0[i])));
        o1[i] = pack2(fmaf(Y[a + 2] - bf_lo(t1), bf_lo(g1[i]), bf_lo(x1[i])), fmaf(Y[a + 3] - bf_hi(t1), bf_hi(g1[i]), bf_hi(x1[i])));
      }
      stg4(p.out + ooff + 32 * G, o0[0], o0[1], o0[2], o0[3]);
      stg4(p.out + ooff + 32 * G + 8 * DM, o1[0], o1[1], o1[2], o1[3]);
    }
    TLC(10);
  }
}

typedef CUresult (*EncFn)(CUtensorMap*, CUtensorMapDataType, cuuint32_t, void*, const cuuint64_t*, const cuuint64_t*, const cuuint32_t*,
                          const cuuint32_t*, CUtensorMapInterleave, CUtensorMapSwizzle, CUtensorMapL2promotion, CUtensorMapFloatOOBfill);

void make_map(EncFn enc, CUtensorMap* m, const void* ptr, int nd, const uint64_t* dims, const uint64_t* strides, const uint32_t* box,
              CUtensorMapSwizzle sw = CU_TENSOR_MAP_SWIZZLE_128B) {
  const cuuint32_t es[5] = {1, 1, 1, 1, 1};
  cuuint64_t d[5], s[5]; cuuint32_t b[5];
  for (int i = 0; i < nd; i++) { d[i] = dims[i]; b[i] = box[i]; if (i + 1 < nd) s[i] = strides[i]; }
  enc(m, CU_TENSOR_MAP_DATA_TYPE_BFLOAT16, nd, const_cast<void*>(ptr), d, s, b, es, CU_TENSOR_MAP_INTERLEAVE_NONE,
      sw, CU_TENSOR_MAP_L2_PROMOTION_L2_128B, CU_TENSOR_MAP_FLOAT_OOB_FILL_NONE);
}

}

extern "C" void kernel_launch(void* const* d_in, const int* in_sizes, int n_in, void* d_out, int out_size) {
  static Params prm;
  static const void* key[11];
  static EncFn enc = nullptr;
  bool same = enc != nullptr && key[10] == d_out;
  for (int i = 0; i < 10 && same; i++) same = key[i] == d_in[i];
  if (!same) {
    if (!enc) {
      cudaDriverEntryPointQueryResult q;
      cudaGetDriverEntryPoint("cuTensorMapEncodeTiled", reinterpret_cast<void**>(&enc), cudaEnableDefault, &q);
      cudaFuncSetAttribute(fused_kernel, cudaFuncAttributeMaxDynamicSharedMemorySize, SMEM_BYTES);
    }
    void *xn, *uv, *h;
    cudaGetSymbolAddress(&xn, g_xn);
    cudaGetSymbolAddress(&uv, g_uv);
    cudaGetSymbolAddress(&h, g_h);
    const uint64_t R = DM * 2;
    const uint32_t box2[2] = {64, 128}, box3[3] = {64, 64, 2}, box5[5] = {64, 2, 4, 4, 2}, boxs[2] = {32, 128};
    { const uint64_t d[2] = {DM, SEQ}, s[1] = {R}; make_map(enc, &prm.mx, d_in[0], 2, d, s, box2); }
    { const uint64_t d[2] = {64, SEQ * 8}, s[1] = {128}; make_map(enc, &prm.mx16, d_in[0], 2, d, s, box2); make_map(enc, &prm.sxn, xn, 2, d, s, box2); }
    { const uint64_t d[3] = {64, SEQ, 8}, s[2] = {R, 128}; make_map(enc, &prm.mxn, xn, 3, d, s, box3); }
    { const uint64_t d[2] = {SEQ, SEQ}, s[1] = {SEQ * 2}; make_map(enc, &prm.mcr, d_in[1], 2, d, s, box2); make_map(enc, &prm.mci, d_in[2], 2, d, s, box2); }
    { const uint64_t d[5] = {DM, 2, 4, 4, DM / 32}, s[4] = {R, 8 * R, 2 * R, 32 * R};
      make_map(enc, &prm.mdre, d_in[3], 5, d, s, box5); make_map(enc, &prm.mdim, d_in[4], 5, d, s, box5); }
    { const uint64_t d[3] = {FF, DM, 2}, s[2] = {FF * 2, 128}; make_map(enc, &prm.mw1, d_in[6], 3, d, s, box3); }
    { const uint64_t d[2] = {FF, SEQ}, s[1] = {FF * 2}; make_map(enc, &prm.mh, h, 2, d, s, box2); make_map(enc, &prm.sh, h, 2, d, s, boxs, CU_TENSOR_MAP_SWIZZLE_NONE); }
    { const uint64_t d[5] = {DM, 2, 4, 4, FF / 32}, s[4] = {R, 8 * R, 2 * R, 32 * R}; make_map(enc, &prm.mw2, d_in[8], 5, d, s, box5); }
    { const uint64_t d[2] = {DM, 2 * SEQ}, s[1] = {R}; make_map(enc, &prm.muv, uv, 2, d, s, box2); make_map(enc, &prm.suv, uv, 2, d, s, boxs, CU_TENSOR_MAP_SWIZZLE_NONE); }
    prm.x = (const __nv_bfloat16*)d_in[0]; prm.w1 = (const __nv_bfloat16*)d_in[6]; prm.b1 = (const __nv_bfloat16*)d_in[7];
    prm.b2 = (const __nv_bfloat16*)d_in[9]; prm.out = (__nv_bfloat16*)d_out;
    for (int i = 0; i < 10; i++) key[i] = d_in[i];
    key[10] = d_out;
  }
  fused_kernel<<<128, 384, SMEM_BYTES>>>(prm);
}
```

```cpp
#include <cuda_runtime.h>
#include <cuda_bf16.h>
#include <cuda.h>
#include <stdint.h>

namespace {

constexpr int SEQ = 2048, DM = 512, FF = 1792;
constexpr int NST = 6;
constexpr int STB = 32768;
constexpr int OFF_STG = NST * STB;
constexpr int OFF_VH = OFF_STG + 32768;
constexpr int OFF_B2 = OFF_VH + 1792;
constexpr int OFF_BAR = OFF_B2 + 256;
constexpr int SMEM_BYTES = OFF_BAR + 336;
static_assert(SMEM_BYTES <= 232448, "smem");
constexpr int BAR_FULL = 0, BAR_EMPTY = 48, BAR_XF = 96, BAR_BF = 160, BAR_BE = 192, BAR_X16 = 224, BAR_V = 232, BAR_FREE = 304,
              BAR_E = 248, BAR_M = 256, BAR_Y = 264, BAR_OK = 272, BAR_DEP = 280, OFF_EPOCH = 288, OFF_STOP = 292, OFF_Z = 296;
__host__ __device__ constexpr int xslot(int k) { return (k < 4 ? k : 2 * k - 4) * 16384; }
__host__ __device__ constexpr int bslot(int i) { return (5 + 2 * i) * 16384; }
constexpr int S_S = 16, S_M = 48, S_Y = 62, S_END = 70;
__host__ __device__ constexpr int stage_of(int s) { return (s - S_S) % NST; }
__host__ __device__ constexpr int par_of(int s) { return ((s - S_S) / NST) & 1; }
constexpr int LAND_STAGE = stage_of(S_END - NST);
#define X16_AT 0
#define PACE_MAX 1500
#define DBG_A 1
#define DBG_B 1
#define PF_NS 700
#define PF_W 7
#define PACE_W 11
#define UVN 4
#define XS0 0
#define HS0 10
#define UNUM 1
#define UDEN 1
__host__ __device__ constexpr int units_done(int s) {
  const int n = s < HS0 ? 0 : s < S_S ? s - HS0 + 1 : (S_S - HS0) + ((s - S_S + 1) * UNUM) / UDEN;
  return n > 28 ? 28 : n;
}
__host__ __device__ constexpr int hvec(int u) { return (u < 16 ? 48 + 4 * u : 4 * (u - 16)) * 16; }
__host__ __device__ constexpr int last_unit_step() { int s = 0; while (units_done(s) < 28) s++; return s; }
constexpr int S_ROLL = last_unit_step() + 1;

constexpr int C_DONE = 0, C_XN = 32, C_H = 64, C_UV = 64 + 16 * 32;

struct Params {
  CUtensorMap mx, mx16, sxn, mxn, mw1, mcr, mci, mh, sh, mw2, muv, suv, mdre, mdim;
  const __nv_bfloat16 *x, *w1, *b1, *b2, *cr, *ci, *dre, *dim, *w2;
  __nv_bfloat16* out;
};

__device__ __align__(1024) __nv_bfloat16 g_xn[SEQ * DM];
__device__ __align__(1024) __nv_bfloat16 g_uv[2 * SEQ * DM];
__device__ __align__(1024) __nv_bfloat16 g_h[SEQ * FF];
__device__ float2 g_stats[SEQ];
__device__ __align__(16) float g_csw[16 * FF];
__device__ unsigned g_cnt[64 + 32 * 32];
__device__ unsigned long long g_pace[8 * 16];
#define TR(step, k) do {} while (0)
#define TLREC(ev) do {} while (0)
#define TLC(ev) do {} while (0)

__device__ __forceinline__ void mbar_init(uint32_t bar, uint32_t cnt) { asm volatile("mbarrier.init.shared::cta.b64 [%0], %1;" :: "r"(bar), "r"(cnt) : "memory"); }
__device__ __forceinline__ void mbar_expect_tx(uint32_t bar, uint32_t bytes) { asm volatile("mbarrier.arrive.expect_tx.shared::cta.b64 _, [%0], %1;" :: "r"(bar), "r"(bytes) : "memory"); }
__device__ __forceinline__ void mbar_arrive(uint32_t bar) { asm volatile("mbarrier.arrive.shared::cta.b64 _, [%0];" :: "r"(bar) : "memory"); }
__device__ __forceinline__ void mbar_arrive_cluster(uint32_t remote_bar) { asm volatile("mbarrier.arrive.shared::cluster.b64 _, [%0];" :: "r"(remote_bar) : "memory"); }
__device__ __forceinline__ uint32_t mapa(uint32_t addr, uint32_t cta) { uint32_t r; asm("mapa.shared::cluster.u32 %0, %1, %2;" : "=r"(r) : "r"(addr), "r"(cta)); return r; }
__device__ __forceinline__ bool mbar_try(uint32_t bar, uint32_t parity) {
  uint32_t ok;
  asm volatile("{\n.reg .pred p;\nmbarrier.try_wait.parity.shared::cta.b64 p, [%1], %2;\nselp.u32 %0, 1, 0, p;\n}" : "=r"(ok) : "r"(bar), "r"(parity) : "memory");
  return ok;
}
__device__ __forceinline__ void mbar_wait(uint32_t bar, uint32_t parity) {
  if (mbar_try(bar, parity)) return;
  for (uint32_t n = 0; n < (1u << 15); n++) if (mbar_try(bar, parity)) break;
}
__device__ __forceinline__ bool elect_one() {
  uint32_t p;
  asm volatile("{\n.reg .pred p;\nelect.sync _|p, 0xffffffff;\nselp.u32 %0, 1, 0, p;\n}" : "=r"(p));
  return p;
}
__device__ __forceinline__ void tma2d(uint32_t dst, const CUtensorMap* m, int c0, int c1, uint32_t bar) {
  asm volatile("cp.async.bulk.tensor.2d.shared::cluster.global.mbarrier::complete_tx::bytes [%0], [%1, {%3, %4}], [%2];"
    :: "r"(dst), "l"(m), "r"(bar), "r"(c0), "r"(c1) : "memory");
}
__device__ __forceinline__ void tma3d(uint32_t dst, const CUtensorMap* m, int c0, int c1, int c2, uint32_t bar) {
  asm volatile("cp.async.bulk.tensor.3d.shared::cluster.global.mbarrier::complete_tx::bytes [%0], [%1, {%3, %4, %5}], [%2];"
    :: "r"(dst), "l"(m), "r"(bar), "r"(c0), "r"(c1), "r"(c2) : "memory");
}
__device__ __forceinline__ void tma5d(uint32_t dst, const CUtensorMap* m, int c0, int c4, uint32_t bar) {
  asm volatile("cp.async.bulk.tensor.5d.shared::cluster.global.mbarrier::complete_tx::bytes [%0], [%1, {%3, %5, %5, %5, %4}], [%2];"
    :: "r"(dst), "l"(m), "r"(bar), "r"(c0), "r"(c4), "r"(0) : "memory");
}
__device__ __forceinline__ void tma_pf2d(const CUtensorMap* m, int c0, int c1) {
  asm volatile("cp.async.bulk.prefetch.tensor.2d.L2.global [%0, {%1, %2}];" :: "l"(m), "r"(c0), "r"(c1) : "memory");
}
__device__ __forceinline__ void wg_fence() { asm volatile("wgmma.fence.sync.aligned;" ::: "memory"); }
__device__ __forceinline__ void wg_commit() { asm volatile("wgmma.commit_group.sync.aligned;" ::: "memory"); }
template <int N> __device__ __forceinline__ void wg_wait() { asm volatile("wgmma.wait_group.sync.aligned %0;" :: "n"(N) : "memory"); }
template <int N> __device__ __forceinline__ void reg_fence(float (&d)[N]) {
#pragma unroll
  for (int i = 0; i < N; i++) asm volatile("" : "+f"(d[i]) :: "memory");
}
__device__ __forceinline__ void wgmma4_n128_tb0(float (&d)[64], uint32_t a, uint32_t b, int scale_d) {
  asm volatile("{\n.reg .pred p;\n.reg .b32 la, lb, hi;\n.reg .b64 da, db;\nsetp.ne.b32 p, %66, 0;\nmov.b32 hi, 0x40000040;\n"
    "add.u32 la, %64, 0;\nadd.u32 lb, %65, 0;\nmov.b64 da, {la, hi};\nmov.b64 db, {lb, hi};\n"
    "wgmma.mma_async.sync.aligned.m64n128k16.f32.bf16.bf16 "
    "{%0, %1, %2, %3, %4, %5, %6, %7, %8, %9, %10, %11, %12, %13, %14, %15, %16, %17, %18, %19, %20, %21, %22, %23, %24, %25, %26, %27, %28, %29, %30, %31, %32, %33, %34, %35, %36, %37, %38, %39, %40, %41, %42, %43, %44, %45, %46, %47, %48, %49, %50, %51, %52, %53, %54, %55, %56, %57, %58, %59, %60, %61, %62, %63}, "
    "da, db, p, 1, 1, 0, 0;\n"
    "add.u32 la, %64, 2;\nadd.u32 lb, %65, 2;\nmov.b64 da, {la, hi};\nmov.b64 db, {lb, hi};\n"
    "wgmma.mma_async.sync.aligned.m64n128k16.f32.bf16.bf16 "
    "{%0, %1, %2, %3, %4, %5, %6, %7, %8, %9, %10, %11, %12, %13, %14, %15, %16, %17, %18, %19, %20, %21, %22, %23, %24, %25, %26, %27, %28, %29, %30, %31, %32, %33, %34, %35, %36, %37, %38, %39, %40, %41, %42, %43, %44, %45, %46, %47, %48, %49, %50, %51, %52, %53, %54, %55, %56, %57, %58, %59, %60, %61, %62, %63}, "
    "da, db, 1, 1, 1, 0, 0;\n"
    "add.u32 la, %64, 4;\nadd.u32 lb, %65, 4;\nmov.b64 da, {la, hi};\nmov.b64 db, {lb, hi};\n"
    "wgmma.mma_async.sync.aligned.m64n128k16.f32.bf16.bf16 "
    "{%0, %1, %2, %3, %4, %5, %6, %7, %8, %9, %10, %11, %12, %13, %14, %15, %16, %17, %18, %19, %20, %21, %22, %23, %24, %25, %26, %27, %28, %29, %30, %31, %32, %33, %34, %35, %36, %37, %38, %39, %40, %41, %42, %43, %44, %45, %46, %47, %48, %49, %50, %51, %52, %53, %54, %55, %56, %57, %58, %59, %60, %61, %62, %63}, "
    "da, db, 1, 1, 1, 0, 0;\n"
    "add.u32 la, %64, 6;\nadd.u32 lb, %65, 6;\nmov.b64 da, {la, hi};\nmov.b64 db, {lb, hi};\n"
    "wgmma.mma_async.sync.aligned.m64n128k16.f32.bf16.bf16 "
    "{%0, %1, %2, %3, %4, %5, %6, %7, %8, %9, %10, %11, %12, %13, %14, %15, %16, %17, %18, %19, %20, %21, %22, %23, %24, %25, %26, %27, %28, %29, %30, %31, %32, %33, %34, %35, %36, %37, %38, %39, %40, %41, %42, %43, %44, %45, %46, %47, %48, %49, %50, %51, %52, %53, %54, %55, %56, %57, %58, %59, %60, %61, %62, %63}, "
    "da, db, 1, 1, 1, 0, 0;\n"
    "}\n"
    : "+f"(d[0]), "+f"(d[1]), "+f"(d[2]), "+f"(d[3]), "+f"(d[4]), "+f"(d[5]), "+f"(d[6]), "+f"(d[7]), "+f"(d[8]), "+f"(d[9]), "+f"(d[10]), "+f"(d[11]), "+f"(d[12]), "+f"(d[13]), "+f"(d[14]), "+f"(d[15]), "+f"(d[16]), "+f"(d[17]), "+f"(d[18]), "+f"(d[19]), "+f"(d[20]), "+f"(d[21]), "+f"(d[22]), "+f"(d[23]), "+f"(d[24]), "+f"(d[25]), "+f"(d[26]), "+f"(d[27]), "+f"(d[28]), "+f"(d[29]), "+f"(d[30]), "+f"(d[31]), "+f"(d[32]), "+f"(d[33]), "+f"(d[34]), "+f"(d[35]), "+f"(d[36]), "+f"(d[37]), "+f"(d[38]), "+f"(d[39]), "+f"(d[40]), "+f"(d[41]), "+f"(d[42]), "+f"(d[43]), "+f"(d[44]), "+f"(d[45]), "+f"(d[46]), "+f"(d[47]), "+f"(d[48]), "+f"(d[49]), "+f"(d[50]), "+f"(d[51]), "+f"(d[52]), "+f"(d[53]), "+f"(d[54]), "+f"(d[55]), "+f"(d[56]), "+f"(d[57]), "+f"(d[58]), "+f"(d[59]), "+f"(d[60]), "+f"(d[61]), "+f"(d[62]), "+f"(d[63])
    : "r"(a), "r"(b), "r"(scale_d));
}
__device__ __forceinline__ void wgmma4_n128_tb1(float (&d)[64], uint32_t a, uint32_t b, int scale_d) {
  asm volatile("{\n.reg .pred p;\n.reg .b32 la, lb, hi;\n.reg .b64 da, db;\nsetp.ne.b32 p, %66, 0;\nmov.b32 hi, 0x40000040;\n"
    "add.u32 la, %64, 0;\nadd.u32 lb, %65, 0;\nmov.b64 da, {la, hi};\nmov.b64 db, {lb, hi};\n"
    "wgmma.mma_async.sync.aligned.m64n128k16.f32.bf16.bf16 "
    "{%0, %1, %2, %3, %4, %5, %6, %7, %8, %9, %10, %11, %12, %13, %14, %15, %16, %17, %18, %19, %20, %21, %22, %23, %24, %25, %26, %27, %28, %29, %30, %31, %32, %33, %34, %35, %36, %37, %38, %39, %40, %41, %42, %43, %44, %45, %46, %47, %48, %49, %50, %51, %52, %53, %54, %55, %56, %57, %58, %59, %60, %61, %62, %63}, "
    "da, db, p, 1, 1, 0, 1;\n"
    "add.u32 la, %64, 2;\nadd.u32 lb, %65, 128;\nmov.b64 da, {la, hi};\nmov.b64 db, {lb, hi};\n"
    "wgmma.mma_async.sync.aligned.m64n128k16.f32.bf16.bf16 "
    "{%0, %1, %2, %3, %4, %5, %6, %7, %8, %9, %10, %11, %12, %13, %14, %15, %16, %17, %18, %19, %20, %21, %22, %23, %24, %25, %26, %27, %28, %29, %30, %31, %32, %33, %34, %35, %36, %37, %38, %39, %40, %41, %42, %43, %44, %45, %46, %47, %48, %49, %50, %51, %52, %53, %54, %55, %56, %57, %58, %59, %60, %61, %62, %63}, "
    "da, db, 1, 1, 1, 0, 1;\n"
    "add.u32 la, %64, 4;\nadd.u32 lb, %65, 256;\nmov.b64 da, {la, hi};\nmov.b64 db, {lb, hi};\n"
    "wgmma.mma_async.sync.aligned.m64n128k16.f32.bf16.bf16 "
    "{%0, %1, %2, %3, %4, %5, %6, %7, %8, %9, %10, %11, %12, %13, %14, %15, %16, %17, %18, %19, %20, %21, %22, %23, %24, %25, %26, %27, %28, %29, %30, %31, %32, %33, %34, %35, %36, %37, %38, %39, %40, %41, %42, %43, %44, %45, %46, %47, %48, %49, %50, %51, %52, %53, %54, %55, %56, %57, %58, %59, %60, %61, %62, %63}, "
    "da, db, 1, 1, 1, 0, 1;\n"
    "add.u32 la, %64, 6;\nadd.u32 lb, %65, 384;\nmov.b64 da, {la, hi};\nmov.b64 db, {lb, hi};\n"
    "wgmma.mma_async.sync.aligned.m64n128k16.f32.bf16.bf16 "
    "{%0, %1, %2, %3, %4, %5, %6, %7, %8, %9, %10, %11, %12, %13, %14, %15, %16, %17, %18, %19, %20, %21, %22, %23, %24, %25, %26, %27, %28, %29, %30, %31, %32, %33, %34, %35, %36, %37, %38, %39, %40, %41, %42, %43, %44, %45, %46, %47, %48, %49, %50, %51, %52, %53, %54, %55, %56, %57, %58, %59, %60, %61, %62, %63}, "
    "da, db, 1, 1, 1, 0, 1;\n"
    "}\n"
    : "+f"(d[0]), "+f"(d[1]), "+f"(d[2]), "+f"(d[3]), "+f"(d[4]), "+f"(d[5]), "+f"(d[6]), "+f"(d[7]), "+f"(d[8]), "+f"(d[9]), "+f"(d[10]), "+f"(d[11]), "+f"(d[12]), "+f"(d[13]), "+f"(d[14]), "+f"(d[15]), "+f"(d[16]), "+f"(d[17]), "+f"(d[18]), "+f"(d[19]), "+f"(d[20]), "+f"(d[21]), "+f"(d[22]), "+f"(d[23]), "+f"(d[24]), "+f"(d[25]), "+f"(d[26]), "+f"(d[27]), "+f"(d[28]), "+f"(d[29]), "+f"(d[30]), "+f"(d[31]), "+f"(d[32]), "+f"(d[33]), "+f"(d[34]), "+f"(d[35]), "+f"(d[36]), "+f"(d[37]), "+f"(d[38]), "+f"(d[39]), "+f"(d[40]), "+f"(d[41]), "+f"(d[42]), "+f"(d[43]), "+f"(d[44]), "+f"(d[45]), "+f"(d[46]), "+f"(d[47]), "+f"(d[48]), "+f"(d[49]), "+f"(d[50]), "+f"(d[51]), "+f"(d[52]), "+f"(d[53]), "+f"(d[54]), "+f"(d[55]), "+f"(d[56]), "+f"(d[57]), "+f"(d[58]), "+f"(d[59]), "+f"(d[60]), "+f"(d[61]), "+f"(d[62]), "+f"(d[63])
    : "r"(a), "r"(b), "r"(scale_d));
}
__device__ __forceinline__ void wgmma4_n96_tb1(float (&d)[48], uint32_t a, uint32_t b, int scale_d) {
  asm volatile("{\n.reg .pred p;\n.reg .b32 la, lb, hi;\n.reg .b64 da, db;\nsetp.ne.b32 p, %50, 0;\nmov.b32 hi, 0x40000040;\n"
    "add.u32 la, %48, 0;\nadd.u32 lb, %49, 0;\nmov.b64 da, {la, hi};\nmov.b64 db, {lb, hi};\n"
    "wgmma.mma_async.sync.aligned.m64n96k16.f32.bf16.bf16 "
    "{%0, %1, %2, %3, %4, %5, %6, %7, %8, %9, %10, %11, %12, %13, %14, %15, %16, %17, %18, %19, %20, %21, %22, %23, %24, %25, %26, %27, %28, %29, %30, %31, %32, %33, %34, %35, %36, %37, %38, %39, %40, %41, %42, %43, %44, %45, %46, %47}, "
    "da, db, p, 1, 1, 0, 1;\n"
    "add.u32 la, %48, 2;\nadd.u32 lb, %49, 128;\nmov.b64 da, {la, hi};\nmov.b64 db, {lb, hi};\n"
    "wgmma.mma_async.sync.aligned.m64n96k16.f32.bf16.bf16 "
    "{%0, %1, %2, %3, %4, %5, %6, %7, %8, %9, %10, %11, %12, %13, %14, %15, %16, %17, %18, %19, %20, %21, %22, %23, %24, %25, %26, %27, %28, %29, %30, %31, %32, %33, %34, %35, %36, %37, %38, %39, %40, %41, %42, %43, %44, %45, %46, %47}, "
    "da, db, 1, 1, 1, 0, 1;\n"
    "add.u32 la, %48, 4;\nadd.u32 lb, %49, 256;\nmov.b64 da, {la, hi};\nmov.b64 db, {lb, hi};\n"
    "wgmma.mma_async.sync.aligned.m64n96k16.f32.bf16.bf16 "
    "{%0, %1, %2, %3, %4, %5, %6, %7, %8, %9, %10, %11, %12, %13, %14, %15, %16, %17, %18, %19, %20, %21, %22, %23, %24, %25, %26, %27, %28, %29, %30, %31, %32, %33, %34, %35, %36, %37, %38, %39, %40, %41, %42, %43, %44, %45, %46, %47}, "
    "da, db, 1, 1, 1, 0, 1;\n"
    "add.u32 la, %48, 6;\nadd.u32 lb, %49, 384;\nmov.b64 da, {la, hi};\nmov.b64 db, {lb, hi};\n"
    "wgmma.mma_async.sync.aligned.m64n96k16.f32.bf16.bf16 "
    "{%0, %1, %2, %3, %4, %5, %6, %7, %8, %9, %10, %11, %12, %13, %14, %15, %16, %17, %18, %19, %20, %21, %22, %23, %24, %25, %26, %27, %28, %29, %30, %31, %32, %33, %34, %35, %36, %37, %38, %39, %40, %41, %42, %43, %44, %45, %46, %47}, "
    "da, db, 1, 1, 1, 0, 1;\n"
    "}\n"
    : "+f"(d[0]), "+f"(d[1]), "+f"(d[2]), "+f"(d[3]), "+f"(d[4]), "+f"(d[5]), "+f"(d[6]), "+f"(d[7]), "+f"(d[8]), "+f"(d[9]), "+f"(d[10]), "+f"(d[11]), "+f"(d[12]), "+f"(d[13]), "+f"(d[14]), "+f"(d[15]), "+f"(d[16]), "+f"(d[17]), "+f"(d[18]), "+f"(d[19]), "+f"(d[20]), "+f"(d[21]), "+f"(d[22]), "+f"(d[23]), "+f"(d[24]), "+f"(d[25]), "+f"(d[26]), "+f"(d[27]), "+f"(d[28]), "+f"(d[29]), "+f"(d[30]), "+f"(d[31]), "+f"(d[32]), "+f"(d[33]), "+f"(d[34]), "+f"(d[35]), "+f"(d[36]), "+f"(d[37]), "+f"(d[38]), "+f"(d[39]), "+f"(d[40]), "+f"(d[41]), "+f"(d[42]), "+f"(d[43]), "+f"(d[44]), "+f"(d[45]), "+f"(d[46]), "+f"(d[47])
    : "r"(a), "r"(b), "r"(scale_d));
}

__device__ __forceinline__ void bar_arrive(int id, int n) { asm volatile("bar.arrive %0, %1;" :: "r"(id), "r"(n) : "memory"); }
__device__ __forceinline__ void bar_sync(int id, int n) { asm volatile("bar.sync %0, %1;" :: "r"(id), "r"(n) : "memory"); }
__device__ __forceinline__ unsigned ld_rlx(const unsigned* p) { unsigned v; asm volatile("ld.relaxed.gpu.global.u32 %0, [%1];" : "=r"(v) : "l"(p) : "memory"); return v; }
__device__ __forceinline__ void red_add(unsigned* p) { asm volatile("red.relaxed.gpu.global.add.u32 [%0], 1;" :: "l"(p) : "memory"); }
__device__ __forceinline__ void wait_cnt(const unsigned* p, unsigned target) {
  for (uint32_t n = 0; n < (1u << 14); n++) if ((int)(ld_rlx(p) - target) >= 0) break;
}
__device__ __forceinline__ float bf_lo(uint32_t v) { return __uint_as_float(v << 16); }
__device__ __forceinline__ float bf_hi(uint32_t v) { return __uint_as_float(v & 0xffff0000u); }
__device__ __forceinline__ uint32_t pack2(float lo, float hi) { uint32_t r; asm("cvt.rn.bf16x2.f32 %0, %1, %2;" : "=r"(r) : "f"(hi), "f"(lo)); return r; }
__device__ __forceinline__ uint32_t pack2v(float lo, float hi) { uint32_t r; asm volatile("cvt.rn.bf16x2.f32 %0, %1, %2;" : "=r"(r) : "f"(hi), "f"(lo)); return r; }
__device__ __forceinline__ float bfr(float v) { return __bfloat162float(__float2bfloat16_rn(v)); }
__device__ __forceinline__ uint32_t tagf(float v, uint32_t tag) { return (__float_as_uint(v) & ~3u) | tag; }
template <int OFF> __device__ __forceinline__ uint4 ld_msg(const void* p) { uint4 v; asm volatile("ld.relaxed.gpu.global.v4.u32 {%0,%1,%2,%3}, [%4 + %5];" : "=r"(v.x), "=r"(v.y), "=r"(v.z), "=r"(v.w) : "l"(p), "n"(OFF) : "memory"); return v; }
__device__ __forceinline__ void st_msg(void* p, uint32_t a, uint32_t b, uint32_t c, uint32_t d) { asm volatile("st.relaxed.gpu.global.v4.u32 [%0], {%1,%2,%3,%4};" :: "l"(p), "r"(a), "r"(b), "r"(c), "r"(d) : "memory"); }
__device__ __forceinline__ uint32_t stale(const uint4& v, uint32_t tag) { return ((v.x ^ tag) | (v.y ^ tag) | (v.z ^ tag) | (v.w ^ tag)) & 3u; }
__device__ __forceinline__ void sts4(uint32_t a, uint32_t x, uint32_t y, uint32_t z, uint32_t w) { asm volatile("st.shared.v4.u32 [%0], {%1,%2,%3,%4};" :: "r"(a), "r"(x), "r"(y), "r"(z), "r"(w) : "memory"); }
__device__ __forceinline__ void tma_st2d(const CUtensorMap* m, uint32_t src, int c0, int c1) {
  asm volatile("cp.async.bulk.tensor.2d.global.shared::cta.bulk_group [%0, {%2, %3}], [%1];" :: "l"(m), "r"(src), "r"(c0), "r"(c1) : "memory");
}
__device__ __forceinline__ void tma_st3d(const CUtensorMap* m, uint32_t src, int c0, int c1, int c2) {
  asm volatile("cp.async.bulk.tensor.3d.global.shared::cta.bulk_group [%0, {%2, %3, %4}], [%1];" :: "l"(m), "r"(src), "r"(c0), "r"(c1), "r"(c2) : "memory");
}
__device__ __forceinline__ float rcp_f(float v) { float r; asm("rcp.approx.f32 %0, %1;" : "=f"(r) : "f"(v)); return r; }
__device__ __forceinline__ float sqrt_f(float v) { float r; asm("sqrt.approx.f32 %0, %1;" : "=f"(r) : "f"(v)); return r; }
__device__ __forceinline__ float tanh_f(float v) { float r; asm("tanh.approx.f32 %0, %1;" : "=f"(r) : "f"(v)); return r; }
__device__ __forceinline__ float gelu_half(float hf) {
  const float k0 = 2.0f * 0.7978845608028654f, k1 = 8.0f * 0.7978845608028654f * 0.044715f;
  return fmaf(hf, tanh_f(hf * fmaf(hf * hf, k1, k0)), hf);
}
__device__ __forceinline__ uint2 ld_msg2(const void* p) { uint2 v; asm volatile("ld.relaxed.gpu.global.v2.u32 {%0,%1}, [%2];" : "=r"(v.x), "=r"(v.y) : "l"(p) : "memory"); return v; }
__device__ __forceinline__ void fence_async_smem() { asm volatile("fence.proxy.async.shared::cta;" ::: "memory"); }
template <int OFF> __device__ __forceinline__ uint4 ldg_nc(const void* p) { uint4 v; asm volatile("ld.global.nc.v4.u32 {%0,%1,%2,%3}, [%4 + %5];" : "=r"(v.x), "=r"(v.y), "=r"(v.z), "=r"(v.w) : "l"(p), "n"(OFF)); return v; }
__device__ __forceinline__ void stg4(void* p, uint32_t a, uint32_t b, uint32_t c, uint32_t d) { asm volatile("st.global.v4.u32 [%0], {%1,%2,%3,%4};" :: "l"(p), "r"(a), "r"(b), "r"(c), "r"(d) : "memory"); }
__device__ __forceinline__ float4 lds4f(uint32_t a) { float4 v; asm volatile("ld.shared.v4.f32 {%0,%1,%2,%3}, [%4];" : "=f"(v.x), "=f"(v.y), "=f"(v.z), "=f"(v.w) : "r"(a)); return v; }
__device__ __forceinline__ uint4 lds4u(uint32_t a) { uint4 v; asm volatile("ld.shared.v4.u32 {%0,%1,%2,%3}, [%4];" : "=r"(v.x), "=r"(v.y), "=r"(v.z), "=r"(v.w) : "r"(a) : "memory"); return v; }
__device__ __forceinline__ float2 lds2f(uint32_t a) { float2 v; asm volatile("ld.shared.v2.f32 {%0,%1}, [%2];" : "=f"(v.x), "=f"(v.y) : "r"(a)); return v; }
__device__ __forceinline__ void st_async4(uint32_t raddr, uint32_t a, uint32_t b, uint32_t c, uint32_t d, uint32_t rbar) {
  asm volatile("st.async.weak.shared::cluster.mbarrier::complete_tx::bytes.v4.b32 [%0], {%1,%2,%3,%4}, [%5];"
    :: "r"(raddr), "r"(a), "r"(b), "r"(c), "r"(d), "r"(rbar) : "memory");
}

struct Ctx {
  uint32_t sm;
  uint32_t da;
  uint32_t db;
  bool lead;
  int trs;
};
template <int V> struct IC { static constexpr int value = V; };
template <int S0, int S1, class F>
__device__ __forceinline__ void static_for(F&& f) {
  if constexpr (S0 < S1) { f(IC<S0>{}); static_for<S0 + 1, S1>(f); }
}
template <int N, int TB>
__device__ __forceinline__ void mma_issue(float (&acc)[N / 2], const Ctx& c, uint32_t offa, uint32_t offb, int accum) {
  const uint32_t a = c.da + (offa >> 4), b = c.db + (offb >> 4) + (TB ? (512u << 16) : (1u << 16));
  wg_fence();
  if constexpr (N == 128 && TB == 0) wgmma4_n128_tb0(acc, a, b, accum);
  if constexpr (N == 128 && TB == 1) wgmma4_n128_tb1(acc, a, b, accum);
  if constexpr (N == 96) wgmma4_n96_tb1(acc, a, b, accum);
  wg_commit();
}
template <int N, int S>
__device__ __forceinline__ void step1(float (&acc)[N / 2], const Ctx& c) {
  if (S < 8) mbar_wait(c.sm + OFF_BAR + BAR_XF + 8 * S, 0);
  mbar_wait(c.sm + OFF_BAR + BAR_BF + 8 * (S & 3), (S >> 2) & 1);
  if (threadIdx.x == 0) TR(S, 3);
  mma_issue<N, 1>(acc, c, xslot(S & 7), bslot(S & 3), (S & 7) != 0);
}
template <int TB>
__device__ __forceinline__ void step2(float (&acc)[64], Ctx& c, int st, uint32_t ph, int accum) {
  mbar_wait(c.sm + OFF_BAR + BAR_FULL + 8 * st, ph);
  mma_issue<128, TB>(acc, c, st * STB, st * STB + 16384, accum);
}
__device__ __forceinline__ void release2(const Ctx& c, int st) {
  if (c.lead) mbar_arrive(c.sm + OFF_BAR + BAR_EMPTY + 8 * st);
}
template <int S>
__device__ __forceinline__ void release(const Ctx& c) {
  if constexpr (S < S_S) {
    if (c.lead) {
      if constexpr (S < 12) mbar_arrive(c.sm + OFF_BAR + BAR_BE + 8 * (S & 3));
      if constexpr (S == 9) mbar_arrive(c.sm + OFF_BAR + BAR_EMPTY);
      if constexpr (S >= 11) mbar_arrive(c.sm + OFF_BAR + BAR_EMPTY + 8 * (S - 10));
    }
  } else if constexpr (S < S_END - NST) {
    release2(c, stage_of(S));
  }
}

struct HEpi { float a0, b0, a1, b1; uint32_t vec, stg, never; uint32_t w0[4], w1[4]; };
template <int G, int I, bool WAIT, int NA>
__device__ __forceinline__ void h_unit(const float (&acc)[NA], HEpi& e, const float4 v, uint32_t free_bar, uint32_t free_par, int bar_id) {
  const int r = 4 * (4 * G + I);
  e.w0[I] = pack2v(gelu_half(fmaf(e.a0, acc[r], fmaf(e.b0, v.x, v.z))), gelu_half(fmaf(e.a0, acc[r + 1], fmaf(e.b0, v.y, v.w))));
  e.w1[I] = pack2v(gelu_half(fmaf(e.a1, acc[r + 2], fmaf(e.b1, v.x, v.z))), gelu_half(fmaf(e.a1, acc[r + 3], fmaf(e.b1, v.y, v.w))));
  if (I < 3)
    asm volatile("{\n.reg .pred p;\nsetp.ne.u32 p, %0, 0;\n@p st.shared.v2.u32 [%1], {%2, %3};\n}" :: "r"(e.never), "r"(e.stg), "r"(e.w0[I]), "r"(e.w1[I]) : "memory");
  if (I == 3) {
    if (WAIT) mbar_wait(free_bar, free_par);
    sts4(e.stg + G * 8192, e.w0[0], e.w0[1], e.w0[2], e.w0[3]);
    sts4(e.stg + G * 8192 + 512, e.w1[0], e.w1[1], e.w1[2], e.w1[3]);
    fence_async_smem();
    bar_arrive(bar_id, 288);
  }
}

__global__ void __cluster_dims__(2, 1, 1) __launch_bounds__(384, 1) fused_kernel(const __grid_constant__ Params p) {
  extern __shared__ __align__(1024) uint8_t smem_raw[];
  const uint32_t sm = (uint32_t)__cvta_generic_to_shared(smem_raw);
  const int tid = threadIdx.x, lane = tid & 31;
  const int warp = __shfl_sync(0xffffffffu, tid >> 5, 0);
  int lc;
  {
    const int c = blockIdx.x >> 1;
    if (c < 4) lc = 4 + c;
    else if (c < 36) lc = ((c - 4) & 7) * 8 + ((c - 4) >> 3);
    else lc = (1 + (c - 36) % 7) * 8 + 4 + (c - 36) / 7;
  }
  int gpc;
  { unsigned smid; asm("mov.u32 %0, %%smid;" : "=r"(smid)); const int t = smid >> 1; gpc = t < 32 ? t & 7 : t < 60 ? 1 + (t - 32) % 7 : t < 62 ? t - 54 : 0; }
  const int rk = blockIdx.x & 1, cb = lc & 3, rb = lc >> 2, j = cb * 2 + rk;
  const int row0 = rb * 128;
  const uint32_t bars = sm + OFF_BAR;
  TLC(0);
#define EPOCH() mbar_wait(bars + BAR_E, 0); unsigned epoch; asm volatile("ld.shared.u32 %0, [%1];" : "=r"(epoch) : "r"(bars + OFF_EPOCH) : "memory"); const uint32_t tag = epoch & 3
  if (warp >= 8) {
    asm volatile("setmaxnreg.dec.sync.aligned.u32 88;");
    if (warp == 8) {
      if (elect_one()) {
        for (int s = 0; s < 8; s++) mbar_init(bars + BAR_XF + 8 * s, 1);
        for (int s = 0; s < 4; s++) { mbar_init(bars + BAR_BF + 8 * s, 1); mbar_init(bars + BAR_BE + 8 * s, 8); }
        mbar_init(bars + BAR_X16, 1);
        fence_async_smem();
        for (int k = 0; k < 8; k++) {
          mbar_expect_tx(bars + BAR_XF + 8 * k, 16384);
          tma2d(sm + xslot(k), &p.mx, k * 64, row0, bars + BAR_XF + 8 * k);
          if (k < 4) {
            mbar_expect_tx(bars + BAR_BF + 8 * k, 16384);
            tma3d(sm + bslot(k), &p.mw1, j * 224 + 96, k * 64, 0, bars + BAR_BF + 8 * k);
          }
          if (k == X16_AT) {
            mbar_expect_tx(bars + BAR_X16, 16384);
            tma2d(sm + OFF_STG, &p.mx16, 0, (row0 + j * 16) * 8, bars + BAR_X16);
          }
        }
        for (int s = 0; s < NST; s++) { mbar_init(bars + BAR_FULL + 8 * s, 1); mbar_init(bars + BAR_EMPTY + 8 * s, 8); }
        mbar_init(bars + BAR_V, 2); for (int s = 0; s < 4; s++) mbar_init(bars + BAR_FREE + 8 * s, 1);
        mbar_init(bars + BAR_E, 1); mbar_init(bars + BAR_DEP, 1);
        mbar_init(bars + BAR_M, 1); mbar_init(bars + BAR_Y, 1); mbar_init(bars + BAR_OK, 8);
        asm volatile("fence.mbarrier_init.release.cluster;" ::: "memory");
        fence_async_smem();
        asm volatile("st.shared.u64 [%0], %1;\nst.shared.u32 [%2], %3;" :: "r"(bars + OFF_Z), "l"(0ull), "r"(bars + OFF_STOP), "r"(0) : "memory");
        mbar_expect_tx(bars + BAR_M, 16384);
        mbar_expect_tx(bars + BAR_Y, 16384);
      }
      __syncwarp();
      __syncthreads();
      asm volatile("barrier.cluster.arrive.relaxed.aligned;" ::: "memory");
      if (elect_one()) {
        const CUtensorMap* mc = rk ? &p.mci : &p.mcr;
        const CUtensorMap* md = rk ? &p.mdim : &p.mdre;
        asm volatile("prefetch.tensormap [%0];" :: "l"(mc) : "memory");
        asm volatile("prefetch.tensormap [%0];" :: "l"(&p.mxn) : "memory");
        asm volatile("prefetch.tensormap [%0];" :: "l"(&p.mh) : "memory");
        asm volatile("prefetch.tensormap [%0];" :: "l"(&p.mw2) : "memory");
        asm volatile("prefetch.tensormap [%0];" :: "l"(&p.muv) : "memory");
        asm volatile("prefetch.tensormap [%0];" :: "l"(md) : "memory");
        unsigned long long* pace = &g_pace[gpc * 16];
        unsigned long long nom = 0;
#define PACE(dt)
        for (int k = 4; k < 16; k++) {
          const uint32_t fb = bars + BAR_BF + 8 * (k & 3);
          mbar_wait(bars + BAR_BE + 8 * (k & 3), ((k >> 2) & 1) ^ 1);
          TR(k, 0); PACE(k < 12 ? 512 : 384); TR(k, 1);
          mbar_expect_tx(fb, 16384);
          tma3d(sm + bslot(k & 3), &p.mw1, j * 224 + (k < 8 ? 96 : 0), (k & 7) * 64, 0, fb);
          if (k == 9) tma_pf2d(mc, cb * 64, row0);
        }
        int st = 0; uint32_t ph = 0;
        int trs = S_S;
#define P_ACQ(dt) mbar_wait(bars + BAR_EMPTY + 8 * st, ph); TR(trs, 0); PACE(dt); TR(trs, 1); trs++; const uint32_t fb = bars + BAR_FULL + 8 * st, sa = sm + st * STB, sb = sa + 16384; mbar_expect_tx(fb, DBG_A * 16384 + DBG_B * 16384)
#define P_ADV() if (++st == NST) { st = 0; ph ^= 1; }
        TLREC(11);
        mbar_wait(bars + BAR_DEP, 0);
        asm volatile("fence.proxy.async.global;" ::: "memory");
        TLREC(12);
        for (int k = 0; k < 32; k++) {
          P_ACQ(k < 2 ? 0 : k < 6 ? 384 : 512); if (DBG_A) tma2d(sa, mc, k * 64, row0, fb); if (DBG_B) tma3d(sb, &p.mxn, 0, k * 64, cb * 2, fb); P_ADV();
        }
        TLREC(13);
        mbar_wait(bars + BAR_DEP, 1);
        asm volatile("fence.proxy.async.global;" ::: "memory");
        TLREC(14);
        const int n0 = cb * 128 + rk * 64, n1 = cb * 128 + (rk ^ 1) * 64;
        for (int k = rk * 14; k < rk * 14 + 14; k++) {
          P_ACQ(512); if (DBG_A) tma2d(sa, &p.mh, k * 64, row0, fb); if (DBG_B) { tma5d(sb, &p.mw2, n0, 2 * k, fb); tma5d(sb + 8192, &p.mw2, n1, 2 * k, fb); } P_ADV();
        }
        TLREC(22);
        mbar_wait(bars + BAR_DEP, 0);
        asm volatile("fence.proxy.async.global;" ::: "memory");
        TLREC(23);
        red_add(&g_cnt[C_DONE]);
#pragma unroll 1
        for (int k = 0; k < 8; k++) {
          P_ACQ(512); if (DBG_A) tma2d(sa, &p.muv, k * 64, rk * SEQ + row0, fb); if (DBG_B) { tma5d(sb, md, k * 64, n0 >> 5, fb); tma5d(sb + 8192, md, k * 64, n1 >> 5, fb); } P_ADV();
        }
        asm volatile("st.volatile.shared.u32 [%0], %1;" :: "r"(bars + OFF_STOP), "r"(1) : "memory");
      }
    } else if (warp == 9) {
      unsigned done0 = 0;
      if (lane == 0) done0 = ld_rlx(&g_cnt[C_DONE]);
      __syncthreads();
      asm volatile("barrier.cluster.arrive.relaxed.aligned;" ::: "memory");
      const unsigned epoch = (done0 >> 7) + 1;
      if (lane == 0) {
        asm volatile("st.shared.u32 [%0], %1;" :: "r"(bars + OFF_EPOCH), "r"(epoch) : "memory");
        mbar_arrive(bars + BAR_E);
        asm volatile("prefetch.tensormap [%0];" :: "l"(&p.sxn) : "memory");
        asm volatile("prefetch.tensormap [%0];" :: "l"(&p.sh) : "memory");
        asm volatile("prefetch.tensormap [%0];" :: "l"(&p.suv) : "memory");
      }
#pragma unroll 1
      for (int ev = 0; ev < 12; ev++) {
        bar_sync(1 + (ev & 3), 288);
        if (lane == 0) {
          const int g = ev < 5 ? ev - 1 : ev < 8 ? ev - 5 : ev - 8;
          if (ev == 0) tma_st2d(&p.sxn, sm + OFF_STG, 0, (row0 + j * 16) * 8);
          else if (ev < 8) tma_st2d(&p.sh, sm + OFF_STG + g * 8192, j * 224 + (ev < 5 ? 96 : 0) + g * 32, row0);
          else tma_st2d(&p.suv, sm + OFF_STG + g * 8192, cb * 128 + g * 32, rk * SEQ + row0);
          asm volatile("cp.async.bulk.commit_group;\ncp.async.bulk.wait_group.read 0;" ::: "memory");
          if (ev == 0) { mbar_arrive(bars + BAR_FREE); mbar_arrive(bars + BAR_FREE + 8); }
          else mbar_arrive(bars + BAR_FREE + 8 * g);
          if (ev == 0 || ev == 7 || ev == 11) {
            unsigned* cnt = &g_cnt[ev == 0 ? C_XN : (ev == 11 ? C_UV : C_H) + rb * 32];
            TLREC(24 + (ev >> 2));
            asm volatile("cp.async.bulk.wait_group 0;" ::: "memory");
            red_add(cnt);
            TLREC(16 + (ev >> 2));
            wait_cnt(cnt, (ev == 0 ? 128 : 8) * epoch);
            mbar_arrive(bars + BAR_DEP);
          }
        }
        __syncwarp();
      }
    } else {
      const int cl = lane < 28 ? lane : 27;
      const __nv_bfloat16* w = p.w1 + (size_t)(rb * 32 + (warp - 10) * 16) * FF + j * 224 + cl * 8;
      __syncthreads();
      asm volatile("barrier.cluster.arrive.relaxed.aligned;" ::: "memory");
      {
        uint4 v[16];
        static_for<0, 16>([&](auto I) { v[decltype(I)::value] = ldg_nc<decltype(I)::value * FF * 2>(w); });
        float s[8] = {0.f, 0.f, 0.f, 0.f, 0.f, 0.f, 0.f, 0.f};
#pragma unroll
        for (int r = 0; r < 16; r++) {
          s[0] += bf_lo(v[r].x); s[1] += bf_hi(v[r].x); s[2] += bf_lo(v[r].y); s[3] += bf_hi(v[r].y);
          s[4] += bf_lo(v[r].z); s[5] += bf_hi(v[r].z); s[6] += bf_lo(v[r].w); s[7] += bf_hi(v[r].w);
        }
        float4* s4 = reinterpret_cast<float4*>(smem_raw + OFF_VH);
        if (warp == 11 && lane < 28) { s4[lane * 2] = make_float4(s[0], s[1], s[2], s[3]); s4[lane * 2 + 1] = make_float4(s[4], s[5], s[6], s[7]); }
        bar_sync(5, 64);
        EPOCH();
        if (warp == 10 && lane < 28) {
          const float4 o0 = s4[lane * 2], o1 = s4[lane * 2 + 1];
          float* dst = &g_csw[rb * FF + j * 224 + lane * 8];
          st_msg(dst, tagf(s[0] + o0.x, tag), tagf(s[1] + o0.y, tag), tagf(s[2] + o0.z, tag), tagf(s[3] + o0.w, tag));
          st_msg(dst + 4, tagf(s[4] + o1.x, tag), tagf(s[5] + o1.y, tag), tagf(s[6] + o1.z, tag), tagf(s[7] + o1.w, tag));
          if (lane == 0) TLREC(15);
        }
        bar_sync(5, 64);
      }
      EPOCH();
      const int q = (warp - 10) * 28 + cl;
      const uint2 bb = *reinterpret_cast<const uint2*>(p.b1 + j * 224 + q * 4);
      if (warp == 11) {
        const uint32_t b2v = *reinterpret_cast<const uint32_t*>(p.b2 + cb * 128 + rk * 64 + lane * 2);
        *reinterpret_cast<float2*>(smem_raw + OFF_B2 + lane * 8) = make_float2(0.5f * bf_lo(b2v), 0.5f * bf_hi(b2v));
      }
      float4 acc;
      for (uint32_t n = 0; n < (1u << 14); n++) {
        uint32_t bad = 0;
        acc = make_float4(0.f, 0.f, 0.f, 0.f);
        uint4 m[16];
        static_for<0, 16>([&](auto I) { m[decltype(I)::value] = ld_msg<decltype(I)::value * FF * 4>(&g_csw[j * 224 + q * 4]); });
#pragma unroll
        for (int r = 0; r < 16; r++) {
          bad |= stale(m[r], tag);
          acc.x += __uint_as_float(m[r].x); acc.y += __uint_as_float(m[r].y); acc.z += __uint_as_float(m[r].z); acc.w += __uint_as_float(m[r].w);
        }
        if (!__any_sync(0xffffffffu, bad)) break;
      }
      if (lane < 28) {
        float4* s4 = reinterpret_cast<float4*>(smem_raw + OFF_VH);
        s4[q * 2] = make_float4(acc.x, acc.y, 0.5f * bf_lo(bb.x), 0.5f * bf_hi(bb.x));
        s4[q * 2 + 1] = make_float4(acc.z, acc.w, 0.5f * bf_lo(bb.y), 0.5f * bf_hi(bb.y));
      }
      __syncwarp();
      if (lane == 0) { mbar_arrive(bars + BAR_V); if (warp == 10) TLREC(20); }
    }
  } else {
    asm volatile("setmaxnreg.inc.sync.aligned.u32 208;");
    __syncthreads();
    asm volatile("barrier.cluster.arrive.relaxed.aligned;" ::: "memory");
    Ctx c; c.sm = sm; c.lead = lane == 0; c.trs = S_S;
    c.da = (((sm + (warp >> 2) * 8192) & 0x3FFFF) >> 4) | (1u << 16); c.db = (sm & 0x3FFFF) >> 4;
    const int rl = warp * 16 + (lane >> 2);
    float Q[64], R[48], U[64], M[64], Y[64];
    HEpi e;
    e.vec = sm + OFF_VH + (lane & 3) * 16; e.stg = sm + OFF_STG + rl * 64 + (lane & 3) * 16;
    e.never = gridDim.y - 1;
    uint2 m0, m1;
    uint32_t xw[4][4];
    float mu[2], qq[2];
    static_for<0, S_ROLL>([&](auto S_) {
      constexpr int S = decltype(S_)::value;
      float4 hv[2];
      if constexpr (S > HS0) static_for<units_done(S - 1), units_done(S)>([&](auto U_) { hv[decltype(U_)::value - units_done(S - 1)] = lds4f(e.vec + hvec(decltype(U_)::value)); });
      if constexpr (S < 8) step1<128, S>(Q, c);
      else if constexpr (S < S_S) step1<96, S>(R, c);
      else step2<1>(U, c, stage_of(S), par_of(S), S > S_S);
      if (S == 0) TLC(1);
      if (S == HS0 - 1) { m0 = ld_msg2(&g_stats[row0 + rl]); m1 = ld_msg2(&g_stats[row0 + rl + 8]); }
      if constexpr (S > 0) { wg_wait<1>(); release<S - 1>(c); }
      if (S == XS0) {
        mbar_wait(bars + BAR_X16, 0);
#pragma unroll
        for (int t = 0; t < 4; t++) {
          const int kc = (t & 1) * 4 + (lane >> 3);
          const uint4 v = lds4u(sm + OFF_STG + (warp * 2 + (t >> 1)) * 1024 + kc * 128 + (((lane & 7) ^ kc) << 4));
          xw[t][0] = v.x; xw[t][1] = v.y; xw[t][2] = v.z; xw[t][3] = v.w;
        }
#pragma unroll
        for (int r = 0; r < 2; r++) {
          float a = 0.f, b = 0.f;
#pragma unroll
          for (int i = 0; i < 8; i++) { a += bf_lo(xw[2 * r + (i >> 2)][i & 3]); b += bf_hi(xw[2 * r + (i >> 2)][i & 3]); }
          mu[r] = a + b;
        }
#pragma unroll
        for (int o = 16; o > 0; o >>= 1) { mu[0] += __shfl_xor_sync(0xffffffffu, mu[0], o); mu[1] += __shfl_xor_sync(0xffffffffu, mu[1], o); }
      }
      if (S == XS0 + 1) {
#pragma unroll
        for (int r = 0; r < 2; r++) {
          mu[r] *= 1.0f / DM;
          const uint32_t mm = pack2(mu[r], mu[r]);
          float a = 0.f, b = 0.f;
#pragma unroll
          for (int i = 0; i < 8; i++) {
            uint32_t& w = xw[2 * r + (i >> 2)][i & 3];
            asm("sub.rn.bf16x2 %0, %0, %1;" : "+r"(w) : "r"(mm));
            a = fmaf(bf_lo(w), bf_lo(w), a); b = fmaf(bf_hi(w), bf_hi(w), b);
          }
          qq[r] = a + b;
        }
#pragma unroll
        for (int o = 16; o > 0; o >>= 1) { qq[0] += __shfl_xor_sync(0xffffffffu, qq[0], o); qq[1] += __shfl_xor_sync(0xffffffffu, qq[1], o); }
      }
      if (S == XS0 + 2) {
        const float mean = (lane & 1) ? mu[1] : mu[0], m1 = bfr(mean), dm = mean - m1;
        const float var = fmaxf(fmaf((lane & 1) ? qq[1] : qq[0], 1.0f / DM, -dm * dm), 0.f);
        const float i1 = rcp_f(bfr(sqrt_f(bfr(bfr(var) + 1e-5f))));
        const float i2 = 0.5f * rcp_f(bfr(sqrt_f(bfr(bfr(var * i1 * i1) + 1e-5f))));
        const float rh = bfr(i1);
        const uint32_t hl = pack2(rh, i1 - rh);
        EPOCH();
        if (lane < 2)
          asm volatile("st.relaxed.gpu.global.v2.u32 [%0], {%1,%2};" :: "l"(&g_stats[row0 + j * 16 + warp * 2 + lane]), "r"(tagf(i1 * i2, tag)), "r"(tagf(-(m1 * i1 + bfr(dm * i1)) * i2, tag)) : "memory");
#pragma unroll
        for (int r = 0; r < 2; r++) {
          const uint32_t t = __shfl_sync(0xffffffffu, hl, r), hi = __byte_perm(t, 0, 0x1010), lo = __byte_perm(t, 0, 0x3232);
#pragma unroll
          for (int i = 0; i < 8; i++) {
            uint32_t& w = xw[2 * r + (i >> 2)][i & 3];
            asm("{\n.reg .b32 t;\nmul.rn.bf16x2 t, %0, %2;\nfma.rn.bf16x2 %0, %0, %1, t;\n}" : "+r"(w) : "r"(hi), "r"(lo));
          }
        }
#pragma unroll
        for (int t = 0; t < 4; t++) {
          const int kc = (t & 1) * 4 + ((lane & 7) >> 1);
          asm volatile("stmatrix.sync.aligned.m8n8.x4.shared.b16 [%0], {%1,%2,%3,%4};"
                       :: "r"(sm + OFF_STG + (warp * 2 + (t >> 1)) * 1024 + kc * 128 + ((((lane & 1) * 4 + (lane >> 3)) ^ kc) << 4)),
                          "r"(xw[t][0]), "r"(xw[t][1]), "r"(xw[t][2]), "r"(xw[t][3]) : "memory");
        }
        fence_async_smem();
        bar_arrive(1, 288);
        TLC(28);
      }
      if (S == 8) { reg_fence(Q); TLC(2); }
      if (S == S_S) { reg_fence(R); TLC(3); }
      if (S == HS0) {
        EPOCH();
        for (uint32_t n = 0; n < (1u << 14) && (((m0.x ^ tag) | (m0.y ^ tag) | (m1.x ^ tag) | (m1.y ^ tag)) & 3u); n++) {
          m0 = ld_msg2(&g_stats[row0 + rl]); m1 = ld_msg2(&g_stats[row0 + rl + 8]);
        }
        e.a0 = __uint_as_float(m0.x); e.b0 = __uint_as_float(m0.y); e.a1 = __uint_as_float(m1.x); e.b1 = __uint_as_float(m1.y);
        mbar_wait(bars + BAR_V, 0);
        TLC(21);
      }
      static_for<units_done(S - 1), units_done(S)>([&](auto U_) {
        constexpr int u = decltype(U_)::value, G = u < 16 ? u / 4 : (u - 16) / 4, ev = 1 + u / 4;
        if (S == HS0) hv[0] = lds4f(e.vec + hvec(u));
        const float4 v = hv[u - units_done(S - 1)];
        if constexpr (u < 16) h_unit<G, u % 4, (G < 2)>(Q, e, v, bars + BAR_FREE + 8 * G, 0, 1 + (ev & 3));
        else h_unit<G, u % 4, true>(R, e, v, bars + BAR_FREE + 8 * G, G < 2, 1 + (ev & 3));
      });
    });
    TLC(4);
    int st = stage_of(S_ROLL), pst = stage_of(S_ROLL - 1); uint32_t ph = par_of(S_ROLL);
#pragma unroll 1
    for (int s = S_ROLL; s < S_M; s++) {
      step2<1>(U, c, st, ph, 1);
      wg_wait<1>();
      release2(c, pst);
      pst = st; if (++st == NST) { st = 0; ph ^= 1; }
    }
    TLC(5);
    static_for<S_M, S_M + UVN>([&](auto S_) {
      constexpr int S = decltype(S_)::value;
      step2<1>(M, c, stage_of(S), par_of(S), S > S_M);
      wg_wait<1>();
      release<S - 1>(c);
      if (S == S_M) reg_fence(U);
      static_for<(S - S_M) * 4 / UVN, (S - S_M + 1) * 4 / UVN>([&](auto G_) {
        constexpr int G = decltype(G_)::value, r = 16 * G;
        mbar_wait(bars + BAR_FREE + 8 * G, G < 2 ? 0 : G == 2 ? 1 : 0);
        sts4(e.stg + G * 8192, pack2(U[r], U[r + 1]), pack2(U[r + 4], U[r + 5]), pack2(U[r + 8], U[r + 9]), pack2(U[r + 12], U[r + 13]));
        sts4(e.stg + G * 8192 + 512, pack2(U[r + 2], U[r + 3]), pack2(U[r + 6], U[r + 7]), pack2(U[r + 10], U[r + 11]), pack2(U[r + 14], U[r + 15]));
        fence_async_smem();
        bar_arrive(1 + G, 288);
      });
    });
    st = stage_of(S_M + UVN); pst = stage_of(S_M + UVN - 1); ph = par_of(S_M + UVN);
#pragma unroll 1
    for (int s = S_M + UVN; s < S_Y; s++) {
      step2<1>(M, c, st, ph, 1);
      wg_wait<1>();
      release2(c, pst);
      pst = st; if (++st == NST) { st = 0; ph ^= 1; }
    }
    TLC(6);
    const size_t ooff = (size_t)(row0 + rl) * DM + cb * 128 + rk * 64 + (lane & 3) * 8;
    const uint32_t mine = warp * 4096 + lane * 16, peer = rk ^ 1, sgn = rk ? 0x80008000u : 0u;
    uint4 g[4], xr[4];
    static_for<S_Y, S_END>([&](auto S_) {
      constexpr int S = decltype(S_)::value;
      step2<0>(Y, c, stage_of(S), par_of(S), S > S_Y);
      wg_wait<1>();
      release<S - 1>(c);
      if (S == S_Y) {
        reg_fence(M);
        asm volatile("barrier.cluster.wait.aligned;" ::: "memory");
        const uint32_t ra = mapa(sm + OFF_STG + mine, peer), rbar = mapa(bars + BAR_M, peer);
#pragma unroll
        for (int v = 0; v < 4; v++)
          st_async4(ra + v * 512, pack2(M[32 + 8 * v], M[33 + 8 * v]), pack2(M[34 + 8 * v], M[35 + 8 * v]), pack2(M[36 + 8 * v], M[37 + 8 * v]), pack2(M[38 + 8 * v], M[39 + 8 * v]), rbar);
        xr[0] = ldg_nc<0>(p.x + ooff); xr[1] = ldg_nc<16 * DM>(p.x + ooff);
        xr[2] = ldg_nc<64>(p.x + ooff); xr[3] = ldg_nc<16 * DM + 64>(p.x + ooff);
      }
      if (S == S_Y + 3) {
        mbar_wait(bars + BAR_M, 0);
#pragma unroll
        for (int v = 0; v < 4; v++) {
          const uint4 t = lds4u(sm + OFF_STG + mine + v * 512);
          M[8 * v] += bf_lo(t.x); M[8 * v + 1] += bf_hi(t.x); M[8 * v + 2] += bf_lo(t.y); M[8 * v + 3] += bf_hi(t.y);
          M[8 * v + 4] += bf_lo(t.z); M[8 * v + 5] += bf_hi(t.z); M[8 * v + 6] += bf_lo(t.w); M[8 * v + 7] += bf_hi(t.w);
        }
      }
      if (S == S_END - NST + 1 && c.lead) mbar_arrive_cluster(mapa(bars + BAR_OK, peer));
      if constexpr (S >= S_Y + 4) {
        constexpr int G = (S - S_Y - 4) >> 1, H = (S - S_Y - 4) & 1;
        uint32_t w[4];
#pragma unroll
        for (int i = 0; i < 4; i++) {
          const float2 b = lds2f(sm + OFF_B2 + (32 * G + 8 * i) * 4 + (lane & 3) * 8);
          const int r = 4 * (4 * G + i) + 2 * H;
          const float z0 = fmaf(M[r], 0.5f, b.x), z1 = fmaf(M[r + 1], 0.5f, b.y);
          w[i] = pack2(fmaf(z0, tanh_f(z0), z0), fmaf(z1, tanh_f(z1), z1)) ^ sgn;
        }
        const uint32_t tb = sm + OFF_STG + warp * 4096 + (2 * G + H) * 512;
        __syncwarp();
        asm volatile("stmatrix.sync.aligned.m8n8.x4.shared.b16 [%0], {%1,%2,%3,%4};"
                     :: "r"(tb + (lane & 7) * 64 + (((lane >> 3) ^ ((lane >> 1) & 3)) << 4)), "r"(w[0]), "r"(w[1]), "r"(w[2]), "r"(w[3]) : "memory");
        __syncwarp();
        g[2 * G + H] = lds4u(tb + (lane >> 2) * 64 + (((lane & 3) ^ ((lane >> 3) & 3)) << 4));
      }
    });
    mbar_wait(bars + BAR_OK, 0);
    const uint32_t rl_ = mapa(sm + LAND_STAGE * STB + mine, peer), rlb = mapa(bars + BAR_Y, peer);
    TLC(7);
    wg_wait<0>();
    reg_fence(Y);
    TLC(8);
#pragma unroll
    for (int v = 0; v < 4; v++)
      st_async4(rl_ + v * 512, pack2(Y[32 + 8 * v], Y[33 + 8 * v]), pack2(Y[34 + 8 * v], Y[35 + 8 * v]), pack2(Y[36 + 8 * v], Y[37 + 8 * v]), pack2(Y[38 + 8 * v], Y[39 + 8 * v]), rlb);
    mbar_wait(bars + BAR_Y, 0);
    TLC(9);
#pragma unroll
    for (int G = 0; G < 2; G++) {
      uint32_t o0[4], o1[4];
      const uint4 tv[2] = {lds4u(sm + LAND_STAGE * STB + mine + 2 * G * 512), lds4u(sm + LAND_STAGE * STB + mine + (2 * G + 1) * 512)};
      const uint32_t g0[4] = {g[2 * G].x, g[2 * G].y, g[2 * G].z, g[2 * G].w}, g1[4] = {g[2 * G + 1].x, g[2 * G + 1].y, g[2 * G + 1].z, g[2 * G + 1].w};
      const uint32_t x0[4] = {xr[2 * G].x, xr[2 * G].y, xr[2 * G].z, xr[2 * G].w}, x1[4] = {xr[2 * G + 1].x, xr[2 * G + 1].y, xr[2 * G + 1].z, xr[2 * G + 1].w};
#pragma unroll
      for (int i = 0; i < 4; i++) {
        const int a = 4 * (4 * G + i);
        const uint32_t t0 = (i & 1) ? tv[i >> 1].z : tv[i >> 1].x, t1 = (i & 1) ? tv[i >> 1].w : tv[i >> 1].y;
        o0[i] = pack2(fmaf(Y[a] - bf_lo(t0), bf_lo(g0[i]), bf_lo(x0[i])), fmaf(Y[a + 1] - bf_hi(t0), bf_hi(g0[i]), bf_hi(x0[i])));
        o1[i] = pack2(fmaf(Y[a + 2] - bf_lo(t1), bf_lo(g1[i]), bf_lo(x1[i])), fmaf(Y[a + 3] - bf_hi(t1), bf_hi(g1[i]), bf_hi(x1[i])));
      }
      stg4(p.out + ooff + 32 * G, o0[0], o0[1], o0[2], o0[3]);
      stg4(p.out + ooff + 32 * G + 8 * DM, o1[0], o1[1], o1[2], o1[3]);
    }
    TLC(10);
  }
}

typedef CUresult (*EncFn)(CUtensorMap*, CUtensorMapDataType, cuuint32_t, void*, const cuuint64_t*, const cuuint64_t*, const cuuint32_t*,
                          const cuuint32_t*, CUtensorMapInterleave, CUtensorMapSwizzle, CUtensorMapL2promotion, CUtensorMapFloatOOBfill);

void make_map(EncFn enc, CUtensorMap* m, const void* ptr, int nd, const uint64_t* dims, const uint64_t* strides, const uint32_t* box,
              CUtensorMapSwizzle sw = CU_TENSOR_MAP_SWIZZLE_128B) {
  const cuuint32_t es[5] = {1, 1, 1, 1, 1};
  cuuint64_t d[5], s[5]; cuuint32_t b[5];
  for (int i = 0; i < nd; i++) { d[i] = dims[i]; b[i] = box[i]; if (i + 1 < nd) s[i] = strides[i]; }
  enc(m, CU_TENSOR_MAP_DATA_TYPE_BFLOAT16, nd, const_cast<void*>(ptr), d, s, b, es, CU_TENSOR_MAP_INTERLEAVE_NONE,
      sw, CU_TENSOR_MAP_L2_PROMOTION_L2_128B, CU_TENSOR_MAP_FLOAT_OOB_FILL_NONE);
}

}

extern "C" void kernel_launch(void* const* d_in, const int* in_sizes, int n_in, void* d_out, int out_size) {
  static Params prm;
  static const void* key[11];
  static EncFn enc = nullptr;
  bool same = enc != nullptr && key[10] == d_out;
  for (int i = 0; i < 10 && same; i++) same = key[i] == d_in[i];
  if (!same) {
    if (!enc) {
      cudaDriverEntryPointQueryResult q;
      cudaGetDriverEntryPoint("cuTensorMapEncodeTiled", reinterpret_cast<void**>(&enc), cudaEnableDefault, &q);
      cudaFuncSetAttribute(fused_kernel, cudaFuncAttributeMaxDynamicSharedMemorySize, SMEM_BYTES);
    }
    void *xn, *uv, *h;
    cudaGetSymbolAddress(&xn, g_xn);
    cudaGetSymbolAddress(&uv, g_uv);
    cudaGetSymbolAddress(&h, g_h);
    const uint64_t R = DM * 2;
    const uint32_t box2[2] = {64, 128}, box3[3] = {64, 64, 2}, box5[5] = {64, 2, 4, 4, 2}, boxs[2] = {32, 128};
    { const uint64_t d[2] = {DM, SEQ}, s[1] = {R}; make_map(enc, &prm.mx, d_in[0], 2, d, s, box2); }
    { const uint64_t d[2] = {64, SEQ * 8}, s[1] = {128}; make_map(enc, &prm.mx16, d_in[0], 2, d, s, box2); make_map(enc, &prm.sxn, xn, 2, d, s, box2); }
    { const uint64_t d[3] = {64, SEQ, 8}, s[2] = {R, 128}; make_map(enc, &prm.mxn, xn, 3, d, s, box3); }
    { const uint64_t d[2] = {SEQ, SEQ}, s[1] = {SEQ * 2}; make_map(enc, &prm.mcr, d_in[1], 2, d, s, box2); make_map(enc, &prm.mci, d_in[2], 2, d, s, box2); }
    { const uint64_t d[5] = {DM, 2, 4, 4, DM / 32}, s[4] = {R, 8 * R, 2 * R, 32 * R};
      make_map(enc, &prm.mdre, d_in[3], 5, d, s, box5); make_map(enc, &prm.mdim, d_in[4], 5, d, s, box5); }
    { const uint64_t d[3] = {FF, DM, 2}, s[2] = {FF * 2, 128}; make_map(enc, &prm.mw1, d_in[6], 3, d, s, box3); }
    { const uint64_t d[2] = {FF, SEQ}, s[1] = {FF * 2}; make_map(enc, &prm.mh, h, 2, d, s, box2); make_map(enc, &prm.sh, h, 2, d, s, boxs, CU_TENSOR_MAP_SWIZZLE_NONE); }
    { const uint64_t d[5] = {DM, 2, 4, 4, FF / 32}, s[4] = {R, 8 * R, 2 * R, 32 * R}; make_map(enc, &prm.mw2, d_in[8], 5, d, s, box5); }
    { const uint64_t d[2] = {DM, 2 * SEQ}, s[1] = {R}; make_map(enc, &prm.muv, uv, 2, d, s, box2); make_map(enc, &prm.suv, uv, 2, d, s, boxs, CU_TENSOR_MAP_SWIZZLE_NONE); }
    prm.x = (const __nv_bfloat16*)d_in[0]; prm.w1 = (const __nv_bfloat16*)d_in[6]; prm.b1 = (const __nv_bfloat16*)d_in[7];
    prm.cr = (const __nv_bfloat16*)d_in[1]; prm.ci = (const __nv_bfloat16*)d_in[2]; prm.dre = (const __nv_bfloat16*)d_in[3];
    prm.dim = (const __nv_bfloat16*)d_in[4]; prm.w2 = (const __nv_bfloat16*)d_in[8];
    prm.b2 = (const __nv_bfloat16*)d_in[9]; prm.out = (__nv_bfloat16*)d_out;
    for (int i = 0; i < 10; i++) key[i] = d_in[i];
    key[10] = d_out;
  }
  fused_kernel<<<128, 384, SMEM_BYTES>>>(prm);
}
```

```cpp
#include <cuda_runtime.h>
#include <cuda_bf16.h>
#include <cuda.h>
#include <stdint.h>

namespace {

constexpr int SEQ = 2048, DM = 512, FF = 1792;
constexpr int NST = 6;
constexpr int STB = 32768;
constexpr int OFF_STG = NST * STB;
constexpr int OFF_VH = OFF_STG + 32768;
constexpr int OFF_B2 = OFF_VH + 1792;
constexpr int OFF_BAR = OFF_B2 + 256;
constexpr int SMEM_BYTES = OFF_BAR + 376;
static_assert(SMEM_BYTES <= 232448, "smem");
constexpr int BAR_FULL = 0, BAR_EMPTY = 48, BAR_XF = 96, BAR_BF = 160, BAR_BE = 336, BAR_X16 = 224, BAR_V = 232, BAR_FREE = 304,
              BAR_E = 248, BAR_M = 256, BAR_Y = 264, BAR_OK = 272, BAR_DEP = 280, OFF_EPOCH = 288, OFF_STOP = 292, OFF_Z = 296;
__host__ __device__ constexpr int xslot(int k) { return (k < 4 ? k : 2 * k - 4) * 16384; }
constexpr int NB1 = 5;
__host__ __device__ constexpr int bslot(int i) { return i == 0 ? 11 * 16384 : i == 4 ? OFF_STG + 16384 : (3 + 2 * i) * 16384; }
constexpr int S_S = 16, S_M = 48, S_Y = 62, S_END = 70;
__host__ __device__ constexpr int stage_of(int s) { return (s - S_S) % NST; }
__host__ __device__ constexpr int par_of(int s) { return ((s - S_S) / NST) & 1; }
constexpr int LAND_STAGE = stage_of(S_END - NST);
#define X16_AT 0
#define PACE_MAX 1500
#define DBG_A 1
#define DBG_B 1
#define PF_NS 700
#define PF_W 7
#define PACE_W 11
#define UVN 4
#define W_DLY 7
#define XS0 0
#define HS0 11
#define UNUM 1
#define UDEN 1
__host__ __device__ constexpr int units_done(int s) {
  const int n = s < HS0 ? 0 : s < S_S ? s - HS0 + 1 : (S_S - HS0) + ((s - S_S + 1) * UNUM) / UDEN;
  return n > 28 ? 28 : n;
}
__host__ __device__ constexpr int hvec(int u) { return (u < 16 ? 48 + 4 * u : 4 * (u - 16)) * 16; }
__host__ __device__ constexpr int last_unit_step() { int s = 0; while (units_done(s) < 28) s++; return s; }
constexpr int S_ROLL = last_unit_step() + 1;

constexpr int C_DONE = 0, C_XN = 32, C_H = 64, C_UV = 64 + 16 * 32;

struct Params {
  CUtensorMap mx, mx16, sxn, mxn, mw1, mcr, mci, mh, sh, mw2, muv, suv, mdre, mdim;
  const __nv_bfloat16 *x, *w1, *b1, *b2, *cr, *ci, *dre, *dim, *w2;
  __nv_bfloat16* out;
};

__device__ __align__(1024) __nv_bfloat16 g_xn[SEQ * DM];
__device__ __align__(1024) __nv_bfloat16 g_uv[2 * SEQ * DM];
__device__ __align__(1024) __nv_bfloat16 g_h[SEQ * FF];
__device__ float2 g_stats[SEQ];
__device__ __align__(16) float g_csw[16 * FF];
__device__ unsigned g_cnt[64 + 32 * 32];
__device__ unsigned long long g_pace[8 * 16];
#define TR(step, k) do {} while (0)
#define TLREC(ev) do {} while (0)
#define TLC(ev) do {} while (0)

__device__ __forceinline__ void mbar_init(uint32_t bar, uint32_t cnt) { asm volatile("mbarrier.init.shared::cta.b64 [%0], %1;" :: "r"(bar), "r"(cnt) : "memory"); }
__device__ __forceinline__ void mbar_expect_tx(uint32_t bar, uint32_t bytes) { asm volatile("mbarrier.arrive.expect_tx.shared::cta.b64 _, [%0], %1;" :: "r"(bar), "r"(bytes) : "memory"); }
__device__ __forceinline__ void mbar_arrive(uint32_t bar) { asm volatile("mbarrier.arrive.shared::cta.b64 _, [%0];" :: "r"(bar) : "memory"); }
__device__ __forceinline__ void mbar_arrive_cluster(uint32_t remote_bar) { asm volatile("mbarrier.arrive.shared::cluster.b64 _, [%0];" :: "r"(remote_bar) : "memory"); }
__device__ __forceinline__ uint32_t mapa(uint32_t addr, uint32_t cta) { uint32_t r; asm("mapa.shared::cluster.u32 %0, %1, %2;" : "=r"(r) : "r"(addr), "r"(cta)); return r; }
__device__ __forceinline__ bool mbar_try(uint32_t bar, uint32_t parity) {
  uint32_t ok;
  asm volatile("{\n.reg .pred p;\nmbarrier.try_wait.parity.shared::cta.b64 p, [%1], %2;\nselp.u32 %0, 1, 0, p;\n}" : "=r"(ok) : "r"(bar), "r"(parity) : "memory");
  return ok;
}
__device__ __forceinline__ void mbar_wait(uint32_t bar, uint32_t parity) {
  if (mbar_try(bar, parity)) return;
  for (uint32_t n = 0; n < (1u << 15); n++) if (mbar_try(bar, parity)) break;
}
__device__ __forceinline__ bool elect_one() {
  uint32_t p;
  asm volatile("{\n.reg .pred p;\nelect.sync _|p, 0xffffffff;\nselp.u32 %0, 1, 0, p;\n}" : "=r"(p));
  return p;
}
__device__ __forceinline__ void tma2d(uint32_t dst, const CUtensorMap* m, int c0, int c1, uint32_t bar) {
  asm volatile("cp.async.bulk.tensor.2d.shared::cluster.global.mbarrier::complete_tx::bytes [%0], [%1, {%3, %4}], [%2];"
    :: "r"(dst), "l"(m), "r"(bar), "r"(c0), "r"(c1) : "memory");
}
__device__ __forceinline__ void tma3d(uint32_t dst, const CUtensorMap* m, int c0, int c1, int c2, uint32_t bar) {
  asm volatile("cp.async.bulk.tensor.3d.shared::cluster.global.mbarrier::complete_tx::bytes [%0], [%1, {%3, %4, %5}], [%2];"
    :: "r"(dst), "l"(m), "r"(bar), "r"(c0), "r"(c1), "r"(c2) : "memory");
}
__device__ __forceinline__ void tma5d(uint32_t dst, const CUtensorMap* m, int c0, int c4, uint32_t bar) {
  asm volatile("cp.async.bulk.tensor.5d.shared::cluster.global.mbarrier::complete_tx::bytes [%0], [%1, {%3, %5, %5, %5, %4}], [%2];"
    :: "r"(dst), "l"(m), "r"(bar), "r"(c0), "r"(c4), "r"(0) : "memory");
}
__device__ __forceinline__ void tma_pf2d(const CUtensorMap* m, int c0, int c1) {
  asm volatile("cp.async.bulk.prefetch.tensor.2d.L2.global [%0, {%1, %2}];" :: "l"(m), "r"(c0), "r"(c1) : "memory");
}
__device__ __forceinline__ void wg_fence() { asm volatile("wgmma.fence.sync.aligned;" ::: "memory"); }
__device__ __forceinline__ void wg_commit() { asm volatile("wgmma.commit_group.sync.aligned;" ::: "memory"); }
template <int N> __device__ __forceinline__ void wg_wait() { asm volatile("wgmma.wait_group.sync.aligned %0;" :: "n"(N) : "memory"); }
template <int N> __device__ __forceinline__ void reg_fence(float (&d)[N]) {
#pragma unroll
  for (int i = 0; i < N; i++) asm volatile("" : "+f"(d[i]) :: "memory");
}
__device__ __forceinline__ void wgmma4_n128_tb0(float (&d)[64], uint32_t a, uint32_t b, int scale_d) {
  asm volatile("{\n.reg .pred p;\n.reg .b32 la, lb, hi;\n.reg .b64 da, db;\nsetp.ne.b32 p, %66, 0;\nmov.b32 hi, 0x40000040;\n"
    "add.u32 la, %64, 0;\nadd.u32 lb, %65, 0;\nmov.b64 da, {la, hi};\nmov.b64 db, {lb, hi};\n"
    "wgmma.mma_async.sync.aligned.m64n128k16.f32.bf16.bf16 "
    "{%0, %1, %2, %3, %4, %5, %6, %7, %8, %9, %10, %11, %12, %13, %14, %15, %16, %17, %18, %19, %20, %21, %22, %23, %24, %25, %26, %27, %28, %29, %30, %31, %32, %33, %34, %35, %36, %37, %38, %39, %40, %41, %42, %43, %44, %45, %46, %47, %48, %49, %50, %51, %52, %53, %54, %55, %56, %57, %58, %59, %60, %61, %62, %63}, "
    "da, db, p, 1, 1, 0, 0;\n"
    "add.u32 la, %64, 2;\nadd.u32 lb, %65, 2;\nmov.b64 da, {la, hi};\nmov.b64 db, {lb, hi};\n"
    "wgmma.mma_async.sync.aligned.m64n128k16.f32.bf16.bf16 "
    "{%0, %1, %2, %3, %4, %5, %6, %7, %8, %9, %10, %11, %12, %13, %14, %15, %16, %17, %18, %19, %20, %21, %22, %23, %24, %25, %26, %27, %28, %29, %30, %31, %32, %33, %34, %35, %36, %37, %38, %39, %40, %41, %42, %43, %44, %45, %46, %47, %48, %49, %50, %51, %52, %53, %54, %55, %56, %57, %58, %59, %60, %61, %62, %63}, "
    "da, db, 1, 1, 1, 0, 0;\n"
    "add.u32 la, %64, 4;\nadd.u32 lb, %65, 4;\nmov.b64 da, {la, hi};\nmov.b64 db, {lb, hi};\n"
    "wgmma.mma_async.sync.aligned.m64n128k16.f32.bf16.bf16 "
    "{%0, %1, %2, %3, %4, %5, %6, %7, %8, %9, %10, %11, %12, %13, %14, %15, %16, %17, %18, %19, %20, %21, %22, %23, %24, %25, %26, %27, %28, %29, %30, %31, %32, %33, %34, %35, %36, %37, %38, %39, %40, %41, %42, %43, %44, %45, %46, %47, %48, %49, %50, %51, %52, %53, %54, %55, %56, %57, %58, %59, %60, %61, %62, %63}, "
    "da, db, 1, 1, 1, 0, 0;\n"
    "add.u32 la, %64, 6;\nadd.u32 lb, %65, 6;\nmov.b64 da, {la, hi};\nmov.b64 db, {lb, hi};\n"
    "wgmma.mma_async.sync.aligned.m64n128k16.f32.bf16.bf16 "
    "{%0, %1, %2, %3, %4, %5, %6, %7, %8, %9, %10, %11, %12, %13, %14, %15, %16, %17, %18, %19, %20, %21, %22, %23, %24, %25, %26, %27, %28, %29, %30, %31, %32, %33, %34, %35, %36, %37, %38, %39, %40, %41, %42, %43, %44, %45, %46, %47, %48, %49, %50, %51, %52, %53, %54, %55, %56, %57, %58, %59, %60, %61, %62, %63}, "
    "da, db, 1, 1, 1, 0, 0;\n"
    "}\n"
    : "+f"(d[0]), "+f"(d[1]), "+f"(d[2]), "+f"(d[3]), "+f"(d[4]), "+f"(d[5]), "+f"(d[6]), "+f"(d[7]), "+f"(d[8]), "+f"(d[9]), "+f"(d[10]), "+f"(d[11]), "+f"(d[12]), "+f"(d[13]), "+f"(d[14]), "+f"(d[15]), "+f"(d[16]), "+f"(d[17]), "+f"(d[18]), "+f"(d[19]), "+f"(d[20]), "+f"(d[21]), "+f"(d[22]), "+f"(d[23]), "+f"(d[24]), "+f"(d[25]), "+f"(d[26]), "+f"(d[27]), "+f"(d[28]), "+f"(d[29]), "+f"(d[30]), "+f"(d[31]), "+f"(d[32]), "+f"(d[33]), "+f"(d[34]), "+f"(d[35]), "+f"(d[36]), "+f"(d[37]), "+f"(d[38]), "+f"(d[39]), "+f"(d[40]), "+f"(d[41]), "+f"(d[42]), "+f"(d[43]), "+f"(d[44]), "+f"(d[45]), "+f"(d[46]), "+f"(d[47]), "+f"(d[48]), "+f"(d[49]), "+f"(d[50]), "+f"(d[51]), "+f"(d[52]), "+f"(d[53]), "+f"(d[54]), "+f"(d[55]), "+f"(d[56]), "+f"(d[57]), "+f"(d[58]), "+f"(d[59]), "+f"(d[60]), "+f"(d[61]), "+f"(d[62]), "+f"(d[63])
    : "r"(a), "r"(b), "r"(scale_d));
}
__device__ __forceinline__ void wgmma4_n128_tb1(float (&d)[64], uint32_t a, uint32_t b, int scale_d) {
  asm volatile("{\n.reg .pred p;\n.reg .b32 la, lb, hi;\n.reg .b64 da, db;\nsetp.ne.b32 p, %66, 0;\nmov.b32 hi, 0x40000040;\n"
    "add.u32 la, %64, 0;\nadd.u32 lb, %65, 0;\nmov.b64 da, {la, hi};\nmov.b64 db, {lb, hi};\n"
    "wgmma.mma_async.sync.aligned.m64n128k16.f32.bf16.bf16 "
    "{%0, %1, %2, %3, %4, %5, %6, %7, %8, %9, %10, %11, %12, %13, %14, %15, %16, %17, %18, %19, %20, %21, %22, %23, %24, %25, %26, %27, %28, %29, %30, %31, %32, %33, %34, %35, %36, %37, %38, %39, %40, %41, %42, %43, %44, %45, %46, %47, %48, %49, %50, %51, %52, %53, %54, %55, %56, %57, %58, %59, %60, %61, %62, %63}, "
    "da, db, p, 1, 1, 0, 1;\n"
    "add.u32 la, %64, 2;\nadd.u32 lb, %65, 128;\nmov.b64 da, {la, hi};\nmov.b64 db, {lb, hi};\n"
    "wgmma.mma_async.sync.aligned.m64n128k16.f32.bf16.bf16 "
    "{%0, %1, %2, %3, %4, %5, %6, %7, %8, %9, %10, %11, %12, %13, %14, %15, %16, %17, %18, %19, %20, %21, %22, %23, %24, %25, %26, %27, %28, %29, %30, %31, %32, %33, %34, %35, %36, %37, %38, %39, %40, %41, %42, %43, %44, %45, %46, %47, %48, %49, %50, %51, %52, %53, %54, %55, %56, %57, %58, %59, %60, %61, %62, %63}, "
    "da, db, 1, 1, 1, 0, 1;\n"
    "add.u32 la, %64, 4;\nadd.u32 lb, %65, 256;\nmov.b64 da, {la, hi};\nmov.b64 db, {lb, hi};\n"
    "wgmma.mma_async.sync.aligned.m64n128k16.f32.bf16.bf16 "
    "{%0, %1, %2, %3, %4, %5, %6, %7, %8, %9, %10, %11, %12, %13, %14, %15, %16, %17, %18, %19, %20, %21, %22, %23, %24, %25, %26, %27, %28, %29, %30, %31, %32, %33, %34, %35, %36, %37, %38, %39, %40, %41, %42, %43, %44, %45, %46, %47, %48, %49, %50, %51, %52, %53, %54, %55, %56, %57, %58, %59, %60, %61, %62, %63}, "
    "da, db, 1, 1, 1, 0, 1;\n"
    "add.u32 la, %64, 6;\nadd.u32 lb, %65, 384;\nmov.b64 da, {la, hi};\nmov.b64 db, {lb, hi};\n"
    "wgmma.mma_async.sync.aligned.m64n128k16.f32.bf16.bf16 "
    "{%0, %1, %2, %3, %4, %5, %6, %7, %8, %9, %10, %11, %12, %13, %14, %15, %16, %17, %18, %19, %20, %21, %22, %23, %24, %25, %26, %27, %28, %29, %30, %31, %32, %33, %34, %35, %36, %37, %38, %39, %40, %41, %42, %43, %44, %45, %46, %47, %48, %49, %50, %51, %52, %53, %54, %55, %56, %57, %58, %59, %60, %61, %62, %63}, "
    "da, db, 1, 1, 1, 0, 1;\n"
    "}\n"
    : "+f"(d[0]), "+f"(d[1]), "+f"(d[2]), "+f"(d[3]), "+f"(d[4]), "+f"(d[5]), "+f"(d[6]), "+f"(d[7]), "+f"(d[8]), "+f"(d[9]), "+f"(d[10]), "+f"(d[11]), "+f"(d[12]), "+f"(d[13]), "+f"(d[14]), "+f"(d[15]), "+f"(d[16]), "+f"(d[17]), "+f"(d[18]), "+f"(d[19]), "+f"(d[20]), "+f"(d[21]), "+f"(d[22]), "+f"(d[23]), "+f"(d[24]), "+f"(d[25]), "+f"(d[26]), "+f"(d[27]), "+f"(d[28]), "+f"(d[29]), "+f"(d[30]), "+f"(d[31]), "+f"(d[32]), "+f"(d[33]), "+f"(d[34]), "+f"(d[35]), "+f"(d[36]), "+f"(d[37]), "+f"(d[38]), "+f"(d[39]), "+f"(d[40]), "+f"(d[41]), "+f"(d[42]), "+f"(d[43]), "+f"(d[44]), "+f"(d[45]), "+f"(d[46]), "+f"(d[47]), "+f"(d[48]), "+f"(d[49]), "+f"(d[50]), "+f"(d[51]), "+f"(d[52]), "+f"(d[53]), "+f"(d[54]), "+f"(d[55]), "+f"(d[56]), "+f"(d[57]), "+f"(d[58]), "+f"(d[59]), "+f"(d[60]), "+f"(d[61]), "+f"(d[62]), "+f"(d[63])
    : "r"(a), "r"(b), "r"(scale_d));
}
__device__ __forceinline__ void wgmma4_n96_tb1(float (&d)[48], uint32_t a, uint32_t b, int scale_d) {
  asm volatile("{\n.reg .pred p;\n.reg .b32 la, lb, hi;\n.reg .b64 da, db;\nsetp.ne.b32 p, %50, 0;\nmov.b32 hi, 0x40000040;\n"
    "add.u32 la, %48, 0;\nadd.u32 lb, %49, 0;\nmov.b64 da, {la, hi};\nmov.b64 db, {lb, hi};\n"
    "wgmma.mma_async.sync.aligned.m64n96k16.f32.bf16.bf16 "
    "{%0, %1, %2, %3, %4, %5, %6, %7, %8, %9, %10, %11, %12, %13, %14, %15, %16, %17, %18, %19, %20, %21, %22, %23, %24, %25, %26, %27, %28, %29, %30, %31, %32, %33, %34, %35, %36, %37, %38, %39, %40, %41, %42, %43, %44, %45, %46, %47}, "
    "da, db, p, 1, 1, 0, 1;\n"
    "add.u32 la, %48, 2;\nadd.u32 lb, %49, 128;\nmov.b64 da, {la, hi};\nmov.b64 db, {lb, hi};\n"
    "wgmma.mma_async.sync.aligned.m64n96k16.f32.bf16.bf16 "
    "{%0, %1, %2, %3, %4, %5, %6, %7, %8, %9, %10, %11, %12, %13, %14, %15, %16, %17, %18, %19, %20, %21, %22, %23, %24, %25, %26, %27, %28, %29, %30, %31, %32, %33, %34, %35, %36, %37, %38, %39, %40, %41, %42, %43, %44, %45, %46, %47}, "
    "da, db, 1, 1, 1, 0, 1;\n"
    "add.u32 la, %48, 4;\nadd.u32 lb, %49, 256;\nmov.b64 da, {la, hi};\nmov.b64 db, {lb, hi};\n"
    "wgmma.mma_async.sync.aligned.m64n96k16.f32.bf16.bf16 "
    "{%0, %1, %2, %3, %4, %5, %6, %7, %8, %9, %10, %11, %12, %13, %14, %15, %16, %17, %18, %19, %20, %21, %22, %23, %24, %25, %26, %27, %28, %29, %30, %31, %32, %33, %34, %35, %36, %37, %38, %39, %40, %41, %42, %43, %44, %45, %46, %47}, "
    "da, db, 1, 1, 1, 0, 1;\n"
    "add.u32 la, %48, 6;\nadd.u32 lb, %49, 384;\nmov.b64 da, {la, hi};\nmov.b64 db, {lb, hi};\n"
    "wgmma.mma_async.sync.aligned.m64n96k16.f32.bf16.bf16 "
    "{%0, %1, %2, %3, %4, %5, %6, %7, %8, %9, %10, %11, %12, %13, %14, %15, %16, %17, %18, %19, %20, %21, %22, %23, %24, %25, %26, %27, %28, %29, %30, %31, %32, %33, %34, %35, %36, %37, %38, %39, %40, %41, %42, %43, %44, %45, %46, %47}, "
    "da, db, 1, 1, 1, 0, 1;\n"
    "}\n"
    : "+f"(d[0]), "+f"(d[1]), "+f"(d[2]), "+f"(d[3]), "+f"(d[4]), "+f"(d[5]), "+f"(d[6]), "+f"(d[7]), "+f"(d[8]), "+f"(d[9]), "+f"(d[10]), "+f"(d[11]), "+f"(d[12]), "+f"(d[13]), "+f"(d[14]), "+f"(d[15]), "+f"(d[16]), "+f"(d[17]), "+f"(d[18]), "+f"(d[19]), "+f"(d[20]), "+f"(d[21]), "+f"(d[22]), "+f"(d[23]), "+f"(d[24]), "+f"(d[25]), "+f"(d[26]), "+f"(d[27]), "+f"(d[28]), "+f"(d[29]), "+f"(d[30]), "+f"(d[31]), "+f"(d[32]), "+f"(d[33]), "+f"(d[34]), "+f"(d[35]), "+f"(d[36]), "+f"(d[37]), "+f"(d[38]), "+f"(d[39]), "+f"(d[40]), "+f"(d[41]), "+f"(d[42]), "+f"(d[43]), "+f"(d[44]), "+f"(d[45]), "+f"(d[46]), "+f"(d[47])
    : "r"(a), "r"(b), "r"(scale_d));
}

__device__ __forceinline__ void bar_arrive(int id, int n) { asm volatile("bar.arrive %0, %1;" :: "r"(id), "r"(n) : "memory"); }
__device__ __forceinline__ void bar_sync(int id, int n) { asm volatile("bar.sync %0, %1;" :: "r"(id), "r"(n) : "memory"); }
__device__ __forceinline__ unsigned ld_rlx(const unsigned* p) { unsigned v; asm volatile("ld.relaxed.gpu.global.u32 %0, [%1];" : "=r"(v) : "l"(p) : "memory"); return v; }
__device__ __forceinline__ void red_add(unsigned* p) { asm volatile("red.relaxed.gpu.global.add.u32 [%0], 1;" :: "l"(p) : "memory"); }
__device__ __forceinline__ void wait_cnt(const unsigned* p, unsigned target) {
  for (uint32_t n = 0; n < (1u << 14); n++) if ((int)(ld_rlx(p) - target) >= 0) break;
}
__device__ __forceinline__ float bf_lo(uint32_t v) { return __uint_as_float(v << 16); }
__device__ __forceinline__ float bf_hi(uint32_t v) { return __uint_as_float(v & 0xffff0000u); }
__device__ __forceinline__ uint32_t pack2(float lo, float hi) { uint32_t r; asm("cvt.rn.bf16x2.f32 %0, %1, %2;" : "=r"(r) : "f"(hi), "f"(lo)); return r; }
__device__ __forceinline__ uint32_t pack2v(float lo, float hi) { uint32_t r; asm volatile("cvt.rn.bf16x2.f32 %0, %1, %2;" : "=r"(r) : "f"(hi), "f"(lo)); return r; }
__device__ __forceinline__ float bfr(float v) { return __bfloat162float(__float2bfloat16_rn(v)); }
__device__ __forceinline__ uint32_t tagf(float v, uint32_t tag) { return (__float_as_uint(v) & ~3u) | tag; }
template <int OFF> __device__ __forceinline__ uint4 ld_msg(const void* p) { uint4 v; asm volatile("ld.relaxed.gpu.global.v4.u32 {%0,%1,%2,%3}, [%4 + %5];" : "=r"(v.x), "=r"(v.y), "=r"(v.z), "=r"(v.w) : "l"(p), "n"(OFF) : "memory"); return v; }
__device__ __forceinline__ void st_msg(void* p, uint32_t a, uint32_t b, uint32_t c, uint32_t d) { asm volatile("st.relaxed.gpu.global.v4.u32 [%0], {%1,%2,%3,%4};" :: "l"(p), "r"(a), "r"(b), "r"(c), "r"(d) : "memory"); }
__device__ __forceinline__ uint32_t stale(const uint4& v, uint32_t tag) { return ((v.x ^ tag) | (v.y ^ tag) | (v.z ^ tag) | (v.w ^ tag)) & 3u; }
__device__ __forceinline__ void sts4(uint32_t a, uint32_t x, uint32_t y, uint32_t z, uint32_t w) { asm volatile("st.shared.v4.u32 [%0], {%1,%2,%3,%4};" :: "r"(a), "r"(x), "r"(y), "r"(z), "r"(w) : "memory"); }
__device__ __forceinline__ void tma_st2d(const CUtensorMap* m, uint32_t src, int c0, int c1) {
  asm volatile("cp.async.bulk.tensor.2d.global.shared::cta.bulk_group [%0, {%2, %3}], [%1];" :: "l"(m), "r"(src), "r"(c0), "r"(c1) : "memory");
}
__device__ __forceinline__ void tma_st3d(const CUtensorMap* m, uint32_t src, int c0, int c1, int c2) {
  asm volatile("cp.async.bulk.tensor.3d.global.shared::cta.bulk_group [%0, {%2, %3, %4}], [%1];" :: "l"(m), "r"(src), "r"(c0), "r"(c1), "r"(c2) : "memory");
}
__device__ __forceinline__ float rcp_f(float v) { float r; asm("rcp.approx.f32 %0, %1;" : "=f"(r) : "f"(v)); return r; }
__device__ __forceinline__ float sqrt_f(float v) { float r; asm("sqrt.approx.f32 %0, %1;" : "=f"(r) : "f"(v)); return r; }
__device__ __forceinline__ float tanh_f(float v) { float r; asm("tanh.approx.f32 %0, %1;" : "=f"(r) : "f"(v)); return r; }
__device__ __forceinline__ float gelu_half(float hf) {
  const float k0 = 2.0f * 0.7978845608028654f, k1 = 8.0f * 0.7978845608028654f * 0.044715f;
  return fmaf(hf, tanh_f(hf * fmaf(hf * hf, k1, k0)), hf);
}
__device__ __forceinline__ uint2 ld_msg2(const void* p) { uint2 v; asm volatile("ld.relaxed.gpu.global.v2.u32 {%0,%1}, [%2];" : "=r"(v.x), "=r"(v.y) : "l"(p) : "memory"); return v; }
__device__ __forceinline__ void fence_async_smem() { asm volatile("fence.proxy.async.shared::cta;" ::: "memory"); }
template <int OFF> __device__ __forceinline__ uint4 ldg_nc(const void* p) { uint4 v; asm volatile("ld.global.nc.v4.u32 {%0,%1,%2,%3}, [%4 + %5];" : "=r"(v.x), "=r"(v.y), "=r"(v.z), "=r"(v.w) : "l"(p), "n"(OFF)); return v; }
template <int OFF> __device__ __forceinline__ uint4 ldg_ord(const void* p) { uint4 v; asm volatile("ld.global.L1::no_allocate.v4.u32 {%0,%1,%2,%3}, [%4 + %5];" : "=r"(v.x), "=r"(v.y), "=r"(v.z), "=r"(v.w) : "l"(p), "n"(OFF) : "memory"); return v; }
__device__ __forceinline__ void stg4(void* p, uint32_t a, uint32_t b, uint32_t c, uint32_t d) { asm volatile("st.global.v4.u32 [%0], {%1,%2,%3,%4};" :: "l"(p), "r"(a), "r"(b), "r"(c), "r"(d) : "memory"); }
__device__ __forceinline__ float4 lds4f(uint32_t a) { float4 v; asm volatile("ld.shared.v4.f32 {%0,%1,%2,%3}, [%4];" : "=f"(v.x), "=f"(v.y), "=f"(v.z), "=f"(v.w) : "r"(a)); return v; }
__device__ __forceinline__ uint4 lds4u(uint32_t a) { uint4 v; asm volatile("ld.shared.v4.u32 {%0,%1,%2,%3}, [%4];" : "=r"(v.x), "=r"(v.y), "=r"(v.z), "=r"(v.w) : "r"(a) : "memory"); return v; }
__device__ __forceinline__ float2 lds2f(uint32_t a) { float2 v; asm volatile("ld.shared.v2.f32 {%0,%1}, [%2];" : "=f"(v.x), "=f"(v.y) : "r"(a)); return v; }
__device__ __forceinline__ void st_async4(uint32_t raddr, uint32_t a, uint32_t b, uint32_t c, uint32_t d, uint32_t rbar) {
  asm volatile("st.async.weak.shared::cluster.mbarrier::complete_tx::bytes.v4.b32 [%0], {%1,%2,%3,%4}, [%5];"
    :: "r"(raddr), "r"(a), "r"(b), "r"(c), "r"(d), "r"(rbar) : "memory");
}

struct Ctx {
  uint32_t sm;
  uint32_t da;
  uint32_t db;
  bool lead;
  int trs;
};
template <int V> struct IC { static constexpr int value = V; };
template <int S0, int S1, class F>
__device__ __forceinline__ void static_for(F&& f) {
  if constexpr (S0 < S1) { f(IC<S0>{}); static_for<S0 + 1, S1>(f); }
}
template <int N, int TB>
__device__ __forceinline__ void mma_issue(float (&acc)[N / 2], const Ctx& c, uint32_t offa, uint32_t offb, int accum) {
  const uint32_t a = c.da + (offa >> 4), b = c.db + (offb >> 4) + (TB ? (512u << 16) : (1u << 16));
  wg_fence();
  if constexpr (N == 128 && TB == 0) wgmma4_n128_tb0(acc, a, b, accum);
  if constexpr (N == 128 && TB == 1) wgmma4_n128_tb1(acc, a, b, accum);
  if constexpr (N == 96) wgmma4_n96_tb1(acc, a, b, accum);
  wg_commit();
}
template <int N, int S>
__device__ __forceinline__ void step1(float (&acc)[N / 2], const Ctx& c) {
  if (S < 8) mbar_wait(c.sm + OFF_BAR + BAR_XF + 8 * S, 0);
  mbar_wait(c.sm + OFF_BAR + BAR_BF + 8 * (S % NB1), (S / NB1) & 1);
  if (threadIdx.x == 0) TR(S, 3);
  mma_issue<N, 1>(acc, c, xslot(S & 7), bslot(S % NB1), (S & 7) != 0);
}
template <int TB>
__device__ __forceinline__ void step2(float (&acc)[64], Ctx& c, int st, uint32_t ph, int accum) {
  mbar_wait(c.sm + OFF_BAR + BAR_FULL + 8 * st, ph);
  mma_issue<128, TB>(acc, c, st * STB, st * STB + 16384, accum);
}
__device__ __forceinline__ void release2(const Ctx& c, int st) {
  if (c.lead) mbar_arrive(c.sm + OFF_BAR + BAR_EMPTY + 8 * st);
}
template <int S>
__device__ __forceinline__ void release(const Ctx& c) {
  if constexpr (S < S_S) {
    if (c.lead) {
      if constexpr (S + NB1 < S_S) mbar_arrive(c.sm + OFF_BAR + BAR_BE + 8 * (S % NB1));
      if constexpr (S == 9) mbar_arrive(c.sm + OFF_BAR + BAR_EMPTY);
      if constexpr (S >= 11) mbar_arrive(c.sm + OFF_BAR + BAR_EMPTY + 8 * (S - 10));
    }
  } else if constexpr (S < S_END - NST) {
    release2(c, stage_of(S));
  }
}

struct HEpi { float a0, b0, a1, b1; uint32_t vec, stg, never; uint32_t w0[4], w1[4]; };
template <int G, int I, bool WAIT, int NA>
__device__ __forceinline__ void h_unit(const float (&acc)[NA], HEpi& e, const float4 v, uint32_t free_bar, uint32_t free_par, int bar_id) {
  const int r = 4 * (4 * G + I);
  e.w0[I] = pack2v(gelu_half(fmaf(e.a0, acc[r], fmaf(e.b0, v.x, v.z))), gelu_half(fmaf(e.a0, acc[r + 1], fmaf(e.b0, v.y, v.w))));
  e.w1[I] = pack2v(gelu_half(fmaf(e.a1, acc[r + 2], fmaf(e.b1, v.x, v.z))), gelu_half(fmaf(e.a1, acc[r + 3], fmaf(e.b1, v.y, v.w))));
  if (I < 3)
    asm volatile("{\n.reg .pred p;\nsetp.ne.u32 p, %0, 0;\n@p st.shared.v2.u32 [%1], {%2, %3};\n}" :: "r"(e.never), "r"(e.stg), "r"(e.w0[I]), "r"(e.w1[I]) : "memory");
  if (I == 3) {
    if (WAIT) mbar_wait(free_bar, free_par);
    sts4(e.stg + G * 8192, e.w0[0], e.w0[1], e.w0[2], e.w0[3]);
    sts4(e.stg + G * 8192 + 512, e.w1[0], e.w1[1], e.w1[2], e.w1[3]);
    fence_async_smem();
    bar_arrive(bar_id, 288);
  }
}

__global__ void __cluster_dims__(2, 1, 1) __launch_bounds__(384, 1) fused_kernel(const __grid_constant__ Params p) {
  extern __shared__ __align__(1024) uint8_t smem_raw[];
  const uint32_t sm = (uint32_t)__cvta_generic_to_shared(smem_raw);
  const int tid = threadIdx.x, lane = tid & 31;
  const int warp = __shfl_sync(0xffffffffu, tid >> 5, 0);
  int lc;
  {
    const int c = blockIdx.x >> 1;
    if (c < 4) lc = 4 + c;
    else if (c < 36) lc = ((c - 4) & 7) * 8 + ((c - 4) >> 3);
    else lc = (1 + (c - 36) % 7) * 8 + 4 + (c - 36) / 7;
  }
  int gpc;
  { unsigned smid; asm("mov.u32 %0, %%smid;" : "=r"(smid)); const int t = smid >> 1; gpc = t < 32 ? t & 7 : t < 60 ? 1 + (t - 32) % 7 : t < 62 ? t - 54 : 0; }
  const int rk = blockIdx.x & 1, cb = lc & 3, rb = lc >> 2, j = cb * 2 + rk;
  const int row0 = rb * 128;
  const uint32_t bars = sm + OFF_BAR;
  TLC(0);
#define EPOCH() mbar_wait(bars + BAR_E, 0); unsigned epoch; asm volatile("ld.shared.u32 %0, [%1];" : "=r"(epoch) : "r"(bars + OFF_EPOCH) : "memory"); const uint32_t tag = epoch & 3
  if (warp >= 8) {
    asm volatile("setmaxnreg.dec.sync.aligned.u32 88;");
    if (warp == 8) {
      if (elect_one()) {
        for (int s = 0; s < 8; s++) mbar_init(bars + BAR_XF + 8 * s, 1);
        for (int s = 0; s < NB1; s++) { mbar_init(bars + BAR_BF + 8 * s, 1); mbar_init(bars + BAR_BE + 8 * s, 8); }
        mbar_init(bars + BAR_X16, 1);
        fence_async_smem();
        for (int k = 0; k < 8; k++) {
          mbar_expect_tx(bars + BAR_XF + 8 * k, 16384);
          tma2d(sm + xslot(k), &p.mx, k * 64, row0, bars + BAR_XF + 8 * k);
          if (k < NB1) {
            mbar_expect_tx(bars + BAR_BF + 8 * k, 16384);
            tma3d(sm + bslot(k), &p.mw1, j * 224 + 96, k * 64, 0, bars + BAR_BF + 8 * k);
          }
          if (k == X16_AT) {
            mbar_expect_tx(bars + BAR_X16, 16384);
            tma2d(sm + OFF_STG, &p.mx16, 0, (row0 + j * 16) * 8, bars + BAR_X16);
          }
        }
        for (int s = 0; s < NST; s++) { mbar_init(bars + BAR_FULL + 8 * s, 1); mbar_init(bars + BAR_EMPTY + 8 * s, 8); }
        mbar_init(bars + BAR_V, 2); for (int s = 0; s < 4; s++) mbar_init(bars + BAR_FREE + 8 * s, 1);
        mbar_init(bars + BAR_E, 1); mbar_init(bars + BAR_DEP, 1);
        mbar_init(bars + BAR_M, 1); mbar_init(bars + BAR_Y, 1); mbar_init(bars + BAR_OK, 8);
        asm volatile("fence.mbarrier_init.release.cluster;" ::: "memory");
        fence_async_smem();
        asm volatile("st.shared.u64 [%0], %1;\nst.shared.u32 [%2], %3;" :: "r"(bars + OFF_Z), "l"(0ull), "r"(bars + OFF_STOP), "r"(0) : "memory");
        mbar_expect_tx(bars + BAR_M, 16384);
        mbar_expect_tx(bars + BAR_Y, 16384);
      }
      __syncwarp();
      __syncthreads();
      asm volatile("barrier.cluster.arrive.relaxed.aligned;" ::: "memory");
      if (elect_one()) {
        const CUtensorMap* mc = rk ? &p.mci : &p.mcr;
        const CUtensorMap* md = rk ? &p.mdim : &p.mdre;
        asm volatile("prefetch.tensormap [%0];" :: "l"(mc) : "memory");
        asm volatile("prefetch.tensormap [%0];" :: "l"(&p.mxn) : "memory");
        asm volatile("prefetch.tensormap [%0];" :: "l"(&p.mh) : "memory");
        asm volatile("prefetch.tensormap [%0];" :: "l"(&p.mw2) : "memory");
        asm volatile("prefetch.tensormap [%0];" :: "l"(&p.muv) : "memory");
        asm volatile("prefetch.tensormap [%0];" :: "l"(md) : "memory");
        unsigned long long* pace = &g_pace[gpc * 16];
        unsigned long long nom = 0;
#define PACE(dt)
        for (int k = NB1, i = 0, par = 0; k < S_S; k++) {
          const uint32_t fb = bars + BAR_BF + 8 * i;
          mbar_wait(bars + BAR_BE + 8 * i, par);
          TR(k, 0); PACE(k - NB1 < 8 ? 512 : 384); TR(k, 1);
          mbar_expect_tx(fb, 16384);
          tma3d(sm + bslot(i), &p.mw1, j * 224 + (k < 8 ? 96 : 0), (k & 7) * 64, 0, fb);
          if (k == 10) tma_pf2d(mc, cb * 64, row0);
          if (++i == NB1) { i = 0; par ^= 1; }
        }
        int st = 0; uint32_t ph = 0;
        int trs = S_S;
#define P_ACQ(dt) mbar_wait(bars + BAR_EMPTY + 8 * st, ph); TR(trs, 0); PACE(dt); TR(trs, 1); trs++; const uint32_t fb = bars + BAR_FULL + 8 * st, sa = sm + st * STB, sb = sa + 16384; mbar_expect_tx(fb, DBG_A * 16384 + DBG_B * 16384)
#define P_ADV() if (++st == NST) { st = 0; ph ^= 1; }
        TLREC(11);
        mbar_wait(bars + BAR_DEP, 0);
        asm volatile("fence.proxy.async.global;" ::: "memory");
        TLREC(12);
        for (int k = 0; k < 32; k++) {
          P_ACQ(k < 2 ? 0 : k < 6 ? 384 : 512); if (DBG_A) tma2d(sa, mc, k * 64, row0, fb); if (DBG_B) tma3d(sb, &p.mxn, 0, k * 64, cb * 2, fb); P_ADV();
        }
        TLREC(13);
        mbar_wait(bars + BAR_DEP, 1);
        asm volatile("fence.proxy.async.global;" ::: "memory");
        TLREC(14);
        const int n0 = cb * 128 + rk * 64, n1 = cb * 128 + (rk ^ 1) * 64;
        for (int k = rk * 14; k < rk * 14 + 14; k++) {
          P_ACQ(512); if (DBG_A) tma2d(sa, &p.mh, k * 64, row0, fb); if (DBG_B) { tma5d(sb, &p.mw2, n0, 2 * k, fb); tma5d(sb + 8192, &p.mw2, n1, 2 * k, fb); } P_ADV();
        }
        TLREC(22);
        mbar_wait(bars + BAR_DEP, 0);
        asm volatile("fence.proxy.async.global;" ::: "memory");
        TLREC(23);
        red_add(&g_cnt[C_DONE]);
#pragma unroll 1
        for (int k = 0; k < 8; k++) {
          P_ACQ(512); if (DBG_A) tma2d(sa, &p.muv, k * 64, rk * SEQ + row0, fb); if (DBG_B) { tma5d(sb, md, k * 64, n0 >> 5, fb); tma5d(sb + 8192, md, k * 64, n1 >> 5, fb); } P_ADV();
        }
        asm volatile("st.volatile.shared.u32 [%0], %1;" :: "r"(bars + OFF_STOP), "r"(1) : "memory");
      }
    } else if (warp == 9) {
      unsigned done0 = 0;
      if (lane == 0) done0 = ld_rlx(&g_cnt[C_DONE]);
      __syncthreads();
      asm volatile("barrier.cluster.arrive.relaxed.aligned;" ::: "memory");
      const unsigned epoch = (done0 >> 7) + 1;
      if (lane == 0) {
        asm volatile("st.shared.u32 [%0], %1;" :: "r"(bars + OFF_EPOCH), "r"(epoch) : "memory");
        mbar_arrive(bars + BAR_E);
        asm volatile("prefetch.tensormap [%0];" :: "l"(&p.sxn) : "memory");
        asm volatile("prefetch.tensormap [%0];" :: "l"(&p.sh) : "memory");
        asm volatile("prefetch.tensormap [%0];" :: "l"(&p.suv) : "memory");
      }
#pragma unroll 1
      for (int ev = 0; ev < 12; ev++) {
        bar_sync(1 + (ev & 3), 288);
        if (lane == 0) {
          const int g = ev < 5 ? ev - 1 : ev < 8 ? ev - 5 : ev - 8;
          if (ev == 0) tma_st2d(&p.sxn, sm + OFF_STG, 0, (row0 + j * 16) * 8);
          else if (ev < 8) tma_st2d(&p.sh, sm + OFF_STG + g * 8192, j * 224 + (ev < 5 ? 96 : 0) + g * 32, row0);
          else tma_st2d(&p.suv, sm + OFF_STG + g * 8192, cb * 128 + g * 32, rk * SEQ + row0);
          asm volatile("cp.async.bulk.commit_group;\ncp.async.bulk.wait_group.read 0;" ::: "memory");
          if (ev == 0) { mbar_arrive(bars + BAR_FREE); mbar_arrive(bars + BAR_FREE + 8); }
          else mbar_arrive(bars + BAR_FREE + 8 * g);
          if (ev == 0 || ev == 7 || ev == 11) {
            unsigned* cnt = &g_cnt[ev == 0 ? C_XN : (ev == 11 ? C_UV : C_H) + rb * 32];
            TLREC(24 + (ev >> 2));
            asm volatile("cp.async.bulk.wait_group 0;" ::: "memory");
            red_add(cnt);
            TLREC(16 + (ev >> 2));
            wait_cnt(cnt, (ev == 0 ? 128 : 8) * epoch);
            mbar_arrive(bars + BAR_DEP);
          }
        }
        __syncwarp();
      }
    } else {
      const int cl = lane < 28 ? lane : 27;
      const __nv_bfloat16* w = p.w1 + (size_t)(rb * 32 + (warp - 10) * 16) * FF + j * 224 + cl * 8;
      __syncthreads();
      asm volatile("barrier.cluster.arrive.relaxed.aligned;" ::: "memory");
      {
        const char* pw = reinterpret_cast<const char*>(p.w1 + (size_t)(rb * 32 + (warp - 10) * 16 + (lane >> 2)) * FF + j * 224) + ((lane & 3) == 3 ? 440 : (lane & 3) * 128);
        asm volatile("prefetch.global.L2 [%0];" :: "l"(pw)); asm volatile("prefetch.global.L2 [%0];" :: "l"(pw + 8 * FF * 2));
      }
      mbar_wait(bars + BAR_XF + 8 * W_DLY, 0);
      {
        uint4 v[16];
        static_for<0, 16>([&](auto I) { v[decltype(I)::value] = ldg_ord<decltype(I)::value * FF * 2>(w); });
        float s[8] = {0.f, 0.f, 0.f, 0.f, 0.f, 0.f, 0.f, 0.f};
#pragma unroll
        for (int r = 0; r < 16; r++) {
          s[0] += bf_lo(v[r].x); s[1] += bf_hi(v[r].x); s[2] += bf_lo(v[r].y); s[3] += bf_hi(v[r].y);
          s[4] += bf_lo(v[r].z); s[5] += bf_hi(v[r].z); s[6] += bf_lo(v[r].w); s[7] += bf_hi(v[r].w);
        }
        float4* s4 = reinterpret_cast<float4*>(smem_raw + OFF_VH);
        if (warp == 11 && lane < 28) { s4[lane * 2] = make_float4(s[0], s[1], s[2], s[3]); s4[lane * 2 + 1] = make_float4(s[4], s[5], s[6], s[7]); }
        bar_sync(5, 64);
        EPOCH();
        if (warp == 10 && lane < 28) {
          const float4 o0 = s4[lane * 2], o1 = s4[lane * 2 + 1];
          float* dst = &g_csw[rb * FF + j * 224 + lane * 8];
          st_msg(dst, tagf(s[0] + o0.x, tag), tagf(s[1] + o0.y, tag), tagf(s[2] + o0.z, tag), tagf(s[3] + o0.w, tag));
          st_msg(dst + 4, tagf(s[4] + o1.x, tag), tagf(s[5] + o1.y, tag), tagf(s[6] + o1.z, tag), tagf(s[7] + o1.w, tag));
          if (lane == 0) TLREC(15);
        }
        bar_sync(5, 64);
      }
      EPOCH();
      const int q = (warp - 10) * 28 + cl;
      const uint2 bb = *reinterpret_cast<const uint2*>(p.b1 + j * 224 + q * 4);
      if (warp == 11) {
        const uint32_t b2v = *reinterpret_cast<const uint32_t*>(p.b2 + cb * 128 + rk * 64 + lane * 2);
        *reinterpret_cast<float2*>(smem_raw + OFF_B2 + lane * 8) = make_float2(0.5f * bf_lo(b2v), 0.5f * bf_hi(b2v));
      }
      float4 acc;
      for (uint32_t n = 0; n < (1u << 14); n++) {
        const uint32_t t = ld_rlx(reinterpret_cast<const unsigned*>(&g_csw[(lane & 15) * FF + j * 224 + 223]));
        if (!__any_sync(0xffffffffu, (t ^ tag) & 3u)) break;
      }
      for (uint32_t n = 0; n < (1u << 14); n++) {
        uint32_t bad = 0;
        acc = make_float4(0.f, 0.f, 0.f, 0.f);
        uint4 m[16];
        static_for<0, 16>([&](auto I) { m[decltype(I)::value] = ld_msg<decltype(I)::value * FF * 4>(&g_csw[j * 224 + q * 4]); });
#pragma unroll
        for (int r = 0; r < 16; r++) {
          bad |= stale(m[r], tag);
          acc.x += __uint_as_float(m[r].x); acc.y += __uint_as_float(m[r].y); acc.z += __uint_as_float(m[r].z); acc.w += __uint_as_float(m[r].w);
        }
        if (!__any_sync(0xffffffffu, bad)) break;
      }
      if (lane < 28) {
        float4* s4 = reinterpret_cast<float4*>(smem_raw + OFF_VH);
        s4[q * 2] = make_float4(acc.x, acc.y, 0.5f * bf_lo(bb.x), 0.5f * bf_hi(bb.x));
        s4[q * 2 + 1] = make_float4(acc.z, acc.w, 0.5f * bf_lo(bb.y), 0.5f * bf_hi(bb.y));
      }
      __syncwarp();
      if (lane == 0) { mbar_arrive(bars + BAR_V); if (warp == 10) TLREC(20); }
    }
  } else {
    asm volatile("setmaxnreg.inc.sync.aligned.u32 208;");
    __syncthreads();
    asm volatile("barrier.cluster.arrive.relaxed.aligned;" ::: "memory");
    Ctx c; c.sm = sm; c.lead = lane == 0; c.trs = S_S;
    c.da = (((sm + (warp >> 2) * 8192) & 0x3FFFF) >> 4) | (1u << 16); c.db = (sm & 0x3FFFF) >> 4;
    const int rl = warp * 16 + (lane >> 2);
    float Q[64], R[48], U[64], M[64], Y[64];
    HEpi e;
    e.vec = sm + OFF_VH + (lane & 3) * 16; e.stg = sm + OFF_STG + rl * 64 + (lane & 3) * 16;
    e.never = gridDim.y - 1;
    uint2 m0, m1;
    uint32_t xw[4][4];
    float mu[2], qq[2];
    static_for<0, S_ROLL>([&](auto S_) {
      constexpr int S = decltype(S_)::value;
      float4 hv[2];
      if constexpr (S > HS0) static_for<units_done(S - 1), units_done(S)>([&](auto U_) { hv[decltype(U_)::value - units_done(S - 1)] = lds4f(e.vec + hvec(decltype(U_)::value)); });
      if constexpr (S < 8) step1<128, S>(Q, c);
      else if constexpr (S < S_S) step1<96, S>(R, c);
      else step2<1>(U, c, stage_of(S), par_of(S), S > S_S);
      if (S == 0) TLC(1);
      if (S == HS0 - 1) { m0 = ld_msg2(&g_stats[row0 + rl]); m1 = ld_msg2(&g_stats[row0 + rl + 8]); }
      if constexpr (S > 0) { wg_wait<1>(); release<S - 1>(c); }
      if (S == XS0) {
        mbar_wait(bars + BAR_X16, 0);
#pragma unroll
        for (int t = 0; t < 4; t++) {
          const int kc = (t & 1) * 4 + (lane >> 3);
          const uint4 v = lds4u(sm + OFF_STG + (warp * 2 + (t >> 1)) * 1024 + kc * 128 + (((lane & 7) ^ kc) << 4));
          xw[t][0] = v.x; xw[t][1] = v.y; xw[t][2] = v.z; xw[t][3] = v.w;
        }
      }
      if constexpr (S == XS0 || S == XS0 + 1) {
        constexpr int r = S - XS0;
        float a = bf_lo(xw[2 * r][0]), b = bf_hi(xw[2 * r][0]);
#pragma unroll
        for (int i = 1; i < 8; i++) { a += bf_lo(xw[2 * r + (i >> 2)][i & 3]); b += bf_hi(xw[2 * r + (i >> 2)][i & 3]); }
        mu[r] = a + b;
        if (r == 0) mu[0] += __shfl_xor_sync(0xffffffffu, mu[0], 16);
        else {
          mu[1] += __shfl_xor_sync(0xffffffffu, mu[1], 16);
#pragma unroll
          for (int o = 8; o > 0; o >>= 1) { mu[0] += __shfl_xor_sync(0xffffffffu, mu[0], o); mu[1] += __shfl_xor_sync(0xffffffffu, mu[1], o); }
        }
      }
      if constexpr (S == XS0 + 2 || S == XS0 + 3) {
        constexpr int r = S - XS0 - 2;
        mu[r] *= 1.0f / DM;
        const uint32_t mm = pack2(mu[r], mu[r]);
        float a = 0.f, b = 0.f;
#pragma unroll
        for (int i = 0; i < 8; i++) {
          uint32_t& w = xw[2 * r + (i >> 2)][i & 3];
          asm("sub.rn.bf16x2 %0, %0, %1;" : "+r"(w) : "r"(mm));
          a = fmaf(bf_lo(w), bf_lo(w), a); b = fmaf(bf_hi(w), bf_hi(w), b);
        }
        qq[r] = a + b;
        if (r == 0) qq[0] += __shfl_xor_sync(0xffffffffu, qq[0], 16);
        else {
          qq[1] += __shfl_xor_sync(0xffffffffu, qq[1], 16);
#pragma unroll
          for (int o = 8; o > 0; o >>= 1) { qq[0] += __shfl_xor_sync(0xffffffffu, qq[0], o); qq[1] += __shfl_xor_sync(0xffffffffu, qq[1], o); }
        }
      }
      if (S == XS0 + 4) {
        const float mean = (lane & 1) ? mu[1] : mu[0], m1 = bfr(mean), dm = mean - m1;
        const float var = fmaxf(fmaf((lane & 1) ? qq[1] : qq[0], 1.0f / DM, -dm * dm), 0.f);
        const float i1 = rcp_f(bfr(sqrt_f(bfr(bfr(var) + 1e-5f))));
        const float i2 = 0.5f * rcp_f(bfr(sqrt_f(bfr(bfr(var * i1 * i1) + 1e-5f))));
        const float rh = bfr(i1);
        const uint32_t hl = pack2(rh, i1 - rh);
        mu[0] = i1 * i2; mu[1] = -(m1 * i1 + bfr(dm * i1)) * i2;
        qq[0] = __uint_as_float(__shfl_sync(0xffffffffu, hl, 0)); qq[1] = __uint_as_float(__shfl_sync(0xffffffffu, hl, 1));
      }
      if (S == XS0 + 5) {
#pragma unroll
        for (int r = 0; r < 2; r++) {
          const uint32_t t = __float_as_uint(qq[r]), hi = __byte_perm(t, 0, 0x1010), lo = __byte_perm(t, 0, 0x3232);
#pragma unroll
          for (int i = 0; i < 8; i++) {
            uint32_t& w = xw[2 * r + (i >> 2)][i & 3];
            asm("{\n.reg .b32 t;\nmul.rn.bf16x2 t, %0, %2;\nfma.rn.bf16x2 %0, %0, %1, t;\n}" : "+r"(w) : "r"(hi), "r"(lo));
          }
        }
#pragma unroll
        for (int t = 0; t < 4; t++) {
          const int kc = (t & 1) * 4 + ((lane & 7) >> 1);
          asm volatile("stmatrix.sync.aligned.m8n8.x4.shared.b16 [%0], {%1,%2,%3,%4};"
                       :: "r"(sm + OFF_STG + (warp * 2 + (t >> 1)) * 1024 + kc * 128 + ((((lane & 1) * 4 + (lane >> 3)) ^ kc) << 4)),
                          "r"(xw[t][0]), "r"(xw[t][1]), "r"(xw[t][2]), "r"(xw[t][3]) : "memory");
        }
        fence_async_smem();
        bar_arrive(1, 288);
        EPOCH();
        if (lane < 2)
          asm volatile("st.relaxed.gpu.global.v2.u32 [%0], {%1,%2};" :: "l"(&g_stats[row0 + j * 16 + warp * 2 + lane]), "r"(tagf(mu[0], tag)), "r"(tagf(mu[1], tag)) : "memory");
        TLC(28);
      }
      if (S == 8) { reg_fence(Q); TLC(2); }
      if (S == S_S) { reg_fence(R); TLC(3); }
      if (S == HS0) {
        EPOCH();
        for (uint32_t n = 0; n < (1u << 14) && (((m0.x ^ tag) | (m0.y ^ tag) | (m1.x ^ tag) | (m1.y ^ tag)) & 3u); n++) {
          m0 = ld_msg2(&g_stats[row0 + rl]); m1 = ld_msg2(&g_stats[row0 + rl + 8]);
        }
        e.a0 = __uint_as_float(m0.x); e.b0 = __uint_as_float(m0.y); e.a1 = __uint_as_float(m1.x); e.b1 = __uint_as_float(m1.y);
        mbar_wait(bars + BAR_V, 0);
        TLC(21);
      }
      static_for<units_done(S - 1), units_done(S)>([&](auto U_) {
        constexpr int u = decltype(U_)::value, G = u < 16 ? u / 4 : (u - 16) / 4, ev = 1 + u / 4;
        if (S == HS0) hv[0] = lds4f(e.vec + hvec(u));
        const float4 v = hv[u - units_done(S - 1)];
        if constexpr (u < 16) h_unit<G, u % 4, (G < 2)>(Q, e, v, bars + BAR_FREE + 8 * G, 0, 1 + (ev & 3));
        else h_unit<G, u % 4, true>(R, e, v, bars + BAR_FREE + 8 * G, G < 2, 1 + (ev & 3));
      });
    });
    TLC(4);
    int st = stage_of(S_ROLL), pst = stage_of(S_ROLL - 1); uint32_t ph = par_of(S_ROLL);
#pragma unroll 1
    for (int s = S_ROLL; s < S_M; s++) {
      step2<1>(U, c, st, ph, 1);
      wg_wait<1>();
      release2(c, pst);
      pst = st; if (++st == NST) { st = 0; ph ^= 1; }
    }
    TLC(5);
    static_for<S_M, S_M + UVN>([&](auto S_) {
      constexpr int S = decltype(S_)::value;
      step2<1>(M, c, stage_of(S), par_of(S), S > S_M);
      wg_wait<1>();
      release<S - 1>(c);
      if (S == S_M) reg_fence(U);
      static_for<(S - S_M) * 4 / UVN, (S - S_M + 1) * 4 / UVN>([&](auto G_) {
        constexpr int G = decltype(G_)::value, r = 16 * G;
        mbar_wait(bars + BAR_FREE + 8 * G, G < 2 ? 0 : G == 2 ? 1 : 0);
        sts4(e.stg + G * 8192, pack2(U[r], U[r + 1]), pack2(U[r + 4], U[r + 5]), pack2(U[r + 8], U[r + 9]), pack2(U[r + 12], U[r + 13]));
        sts4(e.stg + G * 8192 + 512, pack2(U[r + 2], U[r + 3]), pack2(U[r + 6], U[r + 7]), pack2(U[r + 10], U[r + 11]), pack2(U[r + 14], U[r + 15]));
        fence_async_smem();
        bar_arrive(1 + G, 288);
      });
    });
    st = stage_of(S_M + UVN); pst = stage_of(S_M + UVN - 1); ph = par_of(S_M + UVN);
#pragma unroll 1
    for (int s = S_M + UVN; s < S_Y; s++) {
      step2<1>(M, c, st, ph, 1);
      wg_wait<1>();
      release2(c, pst);
      pst = st; if (++st == NST) { st = 0; ph ^= 1; }
    }
    TLC(6);
    const size_t ooff = (size_t)(row0 + rl) * DM + cb * 128 + rk * 64 + (lane & 3) * 8;
    const uint32_t mine = warp * 4096 + lane * 16, peer = rk ^ 1, sgn = rk ? 0x80008000u : 0u;
    uint4 g[4], xr[4];
    static_for<S_Y, S_END>([&](auto S_) {
      constexpr int S = decltype(S_)::value;
      step2<0>(Y, c, stage_of(S), par_of(S), S > S_Y);
      wg_wait<1>();
      release<S - 1>(c);
      if (S == S_Y) {
        reg_fence(M);
        asm volatile("barrier.cluster.wait.aligned;" ::: "memory");
        const uint32_t ra = mapa(sm + OFF_STG + mine, peer), rbar = mapa(bars + BAR_M, peer);
#pragma unroll
        for (int v = 0; v < 4; v++)
          st_async4(ra + v * 512, pack2(M[32 + 8 * v], M[33 + 8 * v]), pack2(M[34 + 8 * v], M[35 + 8 * v]), pack2(M[36 + 8 * v], M[37 + 8 * v]), pack2(M[38 + 8 * v], M[39 + 8 * v]), rbar);
        xr[0] = ldg_nc<0>(p.x + ooff); xr[1] = ldg_nc<16 * DM>(p.x + ooff);
        xr[2] = ldg_nc<64>(p.x + ooff); xr[3] = ldg_nc<16 * DM + 64>(p.x + ooff);
      }
      if (S == S_Y + 3) {
        mbar_wait(bars + BAR_M, 0);
#pragma unroll
        for (int v = 0; v < 4; v++) {
          const uint4 t = lds4u(sm + OFF_STG + mine + v * 512);
          M[8 * v] += bf_lo(t.x); M[8 * v + 1] += bf_hi(t.x); M[8 * v + 2] += bf_lo(t.y); M[8 * v + 3] += bf_hi(t.y);
          M[8 * v + 4] += bf_lo(t.z); M[8 * v + 5] += bf_hi(t.z); M[8 * v + 6] += bf_lo(t.w); M[8 * v + 7] += bf_hi(t.w);
        }
      }
      if (S == S_END - NST + 1 && c.lead) mbar_arrive_cluster(mapa(bars + BAR_OK, peer));
      if constexpr (S >= S_Y + 4) {
        constexpr int G = (S - S_Y - 4) >> 1, H = (S - S_Y - 4) & 1;
        uint32_t w[4];
#pragma unroll
        for (int i = 0; i < 4; i++) {
          const float2 b = lds2f(sm + OFF_B2 + (32 * G + 8 * i) * 4 + (lane & 3) * 8);
          const int r = 4 * (4 * G + i) + 2 * H;
          const float z0 = fmaf(M[r], 0.5f, b.x), z1 = fmaf(M[r + 1], 0.5f, b.y);
          w[i] = pack2(fmaf(z0, tanh_f(z0), z0), fmaf(z1, tanh_f(z1), z1)) ^ sgn;
        }
        const uint32_t tb = sm + OFF_STG + warp * 4096 + (2 * G + H) * 512;
        __syncwarp();
        asm volatile("stmatrix.sync.aligned.m8n8.x4.shared.b16 [%0], {%1,%2,%3,%4};"
                     :: "r"(tb + (lane & 7) * 64 + (((lane >> 3) ^ ((lane >> 1) & 3)) << 4)), "r"(w[0]), "r"(w[1]), "r"(w[2]), "r"(w[3]) : "memory");
        __syncwarp();
        g[2 * G + H] = lds4u(tb + (lane >> 2) * 64 + (((lane & 3) ^ ((lane >> 3) & 3)) << 4));
      }
    });
    mbar_wait(bars + BAR_OK, 0);
    const uint32_t rl_ = mapa(sm + LAND_STAGE * STB + mine, peer), rlb = mapa(bars + BAR_Y, peer);
    TLC(7);
    wg_wait<0>();
    reg_fence(Y);
    TLC(8);
#pragma unroll
    for (int v = 0; v < 4; v++)
      st_async4(rl_ + v * 512, pack2(Y[32 + 8 * v], Y[33 + 8 * v]), pack2(Y[34 + 8 * v], Y[35 + 8 * v]), pack2(Y[36 + 8 * v], Y[37 + 8 * v]), pack2(Y[38 + 8 * v], Y[39 + 8 * v]), rlb);
    mbar_wait(bars + BAR_Y, 0);
    TLC(9);
#pragma unroll
    for (int G = 0; G < 2; G++) {
      uint32_t o0[4], o1[4];
      const uint4 tv[2] = {lds4u(sm + LAND_STAGE * STB + mine + 2 * G * 512), lds4u(sm + LAND_STAGE * STB + mine + (2 * G + 1) * 512)};
      const uint32_t g0[4] = {g[2 * G].x, g[2 * G].y, g[2 * G].z, g[2 * G].w}, g1[4] = {g[2 * G + 1].x, g[2 * G + 1].y, g[2 * G + 1].z, g[2 * G + 1].w};
      const uint32_t x0[4] = {xr[2 * G].x, xr[2 * G].y, xr[2 * G].z, xr[2 * G].w}, x1[4] = {xr[2 * G + 1].x, xr[2 * G + 1].y, xr[2 * G + 1].z, xr[2 * G + 1].w};
#pragma unroll
      for (int i = 0; i < 4; i++) {
        const int a = 4 * (4 * G + i);
        const uint32_t t0 = (i & 1) ? tv[i >> 1].z : tv[i >> 1].x, t1 = (i & 1) ? tv[i >> 1].w : tv[i >> 1].y;
        o0[i] = pack2(fmaf(Y[a] - bf_lo(t0), bf_lo(g0[i]), bf_lo(x0[i])), fmaf(Y[a + 1] - bf_hi(t0), bf_hi(g0[i]), bf_hi(x0[i])));
        o1[i] = pack2(fmaf(Y[a + 2] - bf_lo(t1), bf_lo(g1[i]), bf_lo(x1[i])), fmaf(Y[a + 3] - bf_hi(t1), bf_hi(g1[i]), bf_hi(x1[i])));
      }
      stg4(p.out + ooff + 32 * G, o0[0], o0[1], o0[2], o0[3]);
      stg4(p.out + ooff + 32 * G + 8 * DM, o1[0], o1[1], o1[2], o1[3]);
    }
    TLC(10);
  }
}

typedef CUresult (*EncFn)(CUtensorMap*, CUtensorMapDataType, cuuint32_t, void*, const cuuint64_t*, const cuuint64_t*, const cuuint32_t*,
                          const cuuint32_t*, CUtensorMapInterleave, CUtensorMapSwizzle, CUtensorMapL2promotion, CUtensorMapFloatOOBfill);

void make_map(EncFn enc, CUtensorMap* m, const void* ptr, int nd, const uint64_t* dims, const uint64_t* strides, const uint32_t* box,
              CUtensorMapSwizzle sw = CU_TENSOR_MAP_SWIZZLE_128B) {
  const cuuint32_t es[5] = {1, 1, 1, 1, 1};
  cuuint64_t d[5], s[5]; cuuint32_t b[5];
  for (int i = 0; i < nd; i++) { d[i] = dims[i]; b[i] = box[i]; if (i + 1 < nd) s[i] = strides[i]; }
  enc(m, CU_TENSOR_MAP_DATA_TYPE_BFLOAT16, nd, const_cast<void*>(ptr), d, s, b, es, CU_TENSOR_MAP_INTERLEAVE_NONE,
      sw, CU_TENSOR_MAP_L2_PROMOTION_L2_128B, CU_TENSOR_MAP_FLOAT_OOB_FILL_NONE);
}

}

extern "C" void kernel_launch(void* const* d_in, const int* in_sizes, int n_in, void* d_out, int out_size) {
  static Params prm;
  static const void* key[11];
  static EncFn enc = nullptr;
  bool same = enc != nullptr && key[10] == d_out;
  for (int i = 0; i < 10 && same; i++) same = key[i] == d_in[i];
  if (!same) {
    if (!enc) {
      cudaDriverEntryPointQueryResult q;
      cudaGetDriverEntryPoint("cuTensorMapEncodeTiled", reinterpret_cast<void**>(&enc), cudaEnableDefault, &q);
      cudaFuncSetAttribute(fused_kernel, cudaFuncAttributeMaxDynamicSharedMemorySize, SMEM_BYTES);
    }
    void *xn, *uv, *h;
    cudaGetSymbolAddress(&xn, g_xn);
    cudaGetSymbolAddress(&uv, g_uv);
    cudaGetSymbolAddress(&h, g_h);
    const uint64_t R = DM * 2;
    const uint32_t box2[2] = {64, 128}, box3[3] = {64, 64, 2}, box5[5] = {64, 2, 4, 4, 2}, boxs[2] = {32, 128};
    { const uint64_t d[2] = {DM, SEQ}, s[1] = {R}; make_map(enc, &prm.mx, d_in[0], 2, d, s, box2); }
    { const uint64_t d[2] = {64, SEQ * 8}, s[1] = {128}; make_map(enc, &prm.mx16, d_in[0], 2, d, s, box2); make_map(enc, &prm.sxn, xn, 2, d, s, box2); }
    { const uint64_t d[3] = {64, SEQ, 8}, s[2] = {R, 128}; make_map(enc, &prm.mxn, xn, 3, d, s, box3); }
    { const uint64_t d[2] = {SEQ, SEQ}, s[1] = {SEQ * 2}; make_map(enc, &prm.mcr, d_in[1], 2, d, s, box2); make_map(enc, &prm.mci, d_in[2], 2, d, s, box2); }
    { const uint64_t d[5] = {DM, 2, 4, 4, DM / 32}, s[4] = {R, 8 * R, 2 * R, 32 * R};
      make_map(enc, &prm.mdre, d_in[3], 5, d, s, box5); make_map(enc, &prm.mdim, d_in[4], 5, d, s, box5); }
    { const uint64_t d[3] = {FF, DM, 2}, s[2] = {FF * 2, 128}; make_map(enc, &prm.mw1, d_in[6], 3, d, s, box3); }
    { const uint64_t d[2] = {FF, SEQ}, s[1] = {FF * 2}; make_map(enc, &prm.mh, h, 2, d, s, box2); make_map(enc, &prm.sh, h, 2, d, s, boxs, CU_TENSOR_MAP_SWIZZLE_NONE); }
    { const uint64_t d[5] = {DM, 2, 4, 4, FF / 32}, s[4] = {R, 8 * R, 2 * R, 32 * R}; make_map(enc, &prm.mw2, d_in[8], 5, d, s, box5); }
    { const uint64_t d[2] = {DM, 2 * SEQ}, s[1] = {R}; make_map(enc, &prm.muv, uv, 2, d, s, box2); make_map(enc, &prm.suv, uv, 2, d, s, boxs, CU_TENSOR_MAP_SWIZZLE_NONE); }
    prm.x = (const __nv_bfloat16*)d_in[0]; prm.w1 = (const __nv_bfloat16*)d_in[6]; prm.b1 = (const __nv_bfloat16*)d_in[7];
    prm.cr = (const __nv_bfloat16*)d_in[1]; prm.ci = (const __nv_bfloat16*)d_in[2]; prm.dre = (const __nv_bfloat16*)d_in[3];
    prm.dim = (const __nv_bfloat16*)d_in[4]; prm.w2 = (const __nv_bfloat16*)d_in[8];
    prm.b2 = (const __nv_bfloat16*)d_in[9]; prm.out = (__nv_bfloat16*)d_out;
    for (int i = 0; i < 10; i++) key[i] = d_in[i];
    key[10] = d_out;
  }
  fused_kernel<<<128, 384, SMEM_BYTES>>>(prm);
}
```

```cpp
#include <cuda_runtime.h>
#include <cuda_bf16.h>
#include <cuda.h>
#include <stdint.h>

namespace {

constexpr int SEQ = 2048, DM = 512, FF = 1792;
constexpr int NST = 6;
constexpr int STB = 32768;
constexpr int OFF_STG = NST * STB;
constexpr int OFF_VH = OFF_STG + 32768;
constexpr int OFF_B2 = OFF_VH + 1792;
constexpr int OFF_BAR = OFF_B2 + 256;
constexpr int SMEM_BYTES = OFF_BAR + 376;
static_assert(SMEM_BYTES <= 232448, "smem");
constexpr int BAR_FULL = 0, BAR_EMPTY = 48, BAR_XF = 96, BAR_BF = 160, BAR_BE = 336, BAR_X16 = 224, BAR_V = 232, BAR_FREE = 304,
              BAR_E = 248, BAR_M = 256, BAR_Y = 264, BAR_OK = 272, BAR_DEP = 280, OFF_EPOCH = 288, OFF_STOP = 292, OFF_Z = 296;
__host__ __device__ constexpr int xslot(int k) { return (k < 4 ? k : 2 * k - 4) * 16384; }
constexpr int NB1 = 5;
__host__ __device__ constexpr int bslot(int i) { return i == 0 ? 11 * 16384 : i == 4 ? OFF_STG + 16384 : (3 + 2 * i) * 16384; }
constexpr int S_S = 16, S_M = 48, S_Y = 62, S_END = 70;
__host__ __device__ constexpr int stage_of(int s) { return (s - S_S) % NST; }
__host__ __device__ constexpr int par_of(int s) { return ((s - S_S) / NST) & 1; }
constexpr int LAND_STAGE = stage_of(S_END - NST);
#define X16_AT 0
#define PACE_MAX 1500
#define DBG_A 1
#define DBG_B 1
#define PF_NS 700
#define PF_W 7
#define PACE_W 11
#define UVN 4
#define W_DLY 3
#define SLD 3
#define XS0 0
#define HS0 12
#define UNUM 1
#define UDEN 1
__host__ __device__ constexpr int units_done(int s) {
  const int n = s < HS0 ? 0 : s < S_S ? s - HS0 + 1 : (S_S - HS0) + ((s - S_S + 1) * UNUM) / UDEN;
  return n > 28 ? 28 : n;
}
__host__ __device__ constexpr int hvec(int u) { return (u < 16 ? 48 + 4 * u : 4 * (u - 16)) * 16; }
__host__ __device__ constexpr int last_unit_step() { int s = 0; while (units_done(s) < 28) s++; return s; }
constexpr int S_ROLL = last_unit_step() + 1;

constexpr int C_DONE = 0, C_XN = 32, C_H = 160, C_UV = 160 + 16 * 32;

struct Params {
  CUtensorMap mx, mx16, sxn, mxn, mw1, mcr, mci, mh, sh, mw2, muv, suv, mdre, mdim;
  const __nv_bfloat16 *x, *w1, *b1, *b2, *cr, *ci, *dre, *dim, *w2;
  __nv_bfloat16* out;
};

__device__ __align__(1024) __nv_bfloat16 g_xn[SEQ * DM];
__device__ __align__(1024) __nv_bfloat16 g_uv[2 * SEQ * DM];
__device__ __align__(1024) __nv_bfloat16 g_h[SEQ * FF];
__device__ float2 g_stats[SEQ];
__device__ __align__(16) float g_csw[16 * FF];
__device__ __align__(128) unsigned g_cnt[160 + 32 * 32];
__device__ unsigned long long g_pace[8 * 16];
#define TR(step, k) do {} while (0)
#define TLREC(ev) do {} while (0)
#define TLC(ev) do {} while (0)

__device__ __forceinline__ void mbar_init(uint32_t bar, uint32_t cnt) { asm volatile("mbarrier.init.shared::cta.b64 [%0], %1;" :: "r"(bar), "r"(cnt) : "memory"); }
__device__ __forceinline__ void mbar_expect_tx(uint32_t bar, uint32_t bytes) { asm volatile("mbarrier.arrive.expect_tx.shared::cta.b64 _, [%0], %1;" :: "r"(bar), "r"(bytes) : "memory"); }
__device__ __forceinline__ void mbar_arrive(uint32_t bar) { asm volatile("mbarrier.arrive.shared::cta.b64 _, [%0];" :: "r"(bar) : "memory"); }
__device__ __forceinline__ void mbar_arrive_cluster(uint32_t remote_bar) { asm volatile("mbarrier.arrive.shared::cluster.b64 _, [%0];" :: "r"(remote_bar) : "memory"); }
__device__ __forceinline__ uint32_t mapa(uint32_t addr, uint32_t cta) { uint32_t r; asm("mapa.shared::cluster.u32 %0, %1, %2;" : "=r"(r) : "r"(addr), "r"(cta)); return r; }
__device__ __forceinline__ bool mbar_try(uint32_t bar, uint32_t parity) {
  uint32_t ok;
  asm volatile("{\n.reg .pred p;\nmbarrier.try_wait.parity.shared::cta.b64 p, [%1], %2;\nselp.u32 %0, 1, 0, p;\n}" : "=r"(ok) : "r"(bar), "r"(parity) : "memory");
  return ok;
}
__device__ __forceinline__ void mbar_wait(uint32_t bar, uint32_t parity) {
  if (mbar_try(bar, parity)) return;
  for (uint32_t n = 0; n < (1u << 15); n++) if (mbar_try(bar, parity)) break;
}
__device__ __forceinline__ bool elect_one() {
  uint32_t p;
  asm volatile("{\n.reg .pred p;\nelect.sync _|p, 0xffffffff;\nselp.u32 %0, 1, 0, p;\n}" : "=r"(p));
  return p;
}
__device__ __forceinline__ void tma2d(uint32_t dst, const CUtensorMap* m, int c0, int c1, uint32_t bar) {
  asm volatile("cp.async.bulk.tensor.2d.shared::cluster.global.mbarrier::complete_tx::bytes [%0], [%1, {%3, %4}], [%2];"
    :: "r"(dst), "l"(m), "r"(bar), "r"(c0), "r"(c1) : "memory");
}
__device__ __forceinline__ void tma3d(uint32_t dst, const CUtensorMap* m, int c0, int c1, int c2, uint32_t bar) {
  asm volatile("cp.async.bulk.tensor.3d.shared::cluster.global.mbarrier::complete_tx::bytes [%0], [%1, {%3, %4, %5}], [%2];"
    :: "r"(dst), "l"(m), "r"(bar), "r"(c0), "r"(c1), "r"(c2) : "memory");
}
__device__ __forceinline__ void tma5d(uint32_t dst, const CUtensorMap* m, int c0, int c4, uint32_t bar) {
  asm volatile("cp.async.bulk.tensor.5d.shared::cluster.global.mbarrier::complete_tx::bytes [%0], [%1, {%3, %5, %5, %5, %4}], [%2];"
    :: "r"(dst), "l"(m), "r"(bar), "r"(c0), "r"(c4), "r"(0) : "memory");
}
__device__ __forceinline__ void tma_pf2d(const CUtensorMap* m, int c0, int c1) {
  asm volatile("cp.async.bulk.prefetch.tensor.2d.L2.global [%0, {%1, %2}];" :: "l"(m), "r"(c0), "r"(c1) : "memory");
}
__device__ __forceinline__ void wg_fence() { asm volatile("wgmma.fence.sync.aligned;" ::: "memory"); }
__device__ __forceinline__ void wg_commit() { asm volatile("wgmma.commit_group.sync.aligned;" ::: "memory"); }
template <int N> __device__ __forceinline__ void wg_wait() { asm volatile("wgmma.wait_group.sync.aligned %0;" :: "n"(N) : "memory"); }
template <int N> __device__ __forceinline__ void reg_fence(float (&d)[N]) {
#pragma unroll
  for (int i = 0; i < N; i++) asm volatile("" : "+f"(d[i]) :: "memory");
}
__device__ __forceinline__ void wgmma4_n128_tb0(float (&d)[64], uint32_t a, uint32_t b, int scale_d) {
  asm volatile("{\n.reg .pred p;\n.reg .b32 la, lb, hi;\n.reg .b64 da, db;\nsetp.ne.b32 p, %66, 0;\nmov.b32 hi, 0x40000040;\n"
    "add.u32 la, %64, 0;\nadd.u32 lb, %65, 0;\nmov.b64 da, {la, hi};\nmov.b64 db, {lb, hi};\n"
    "wgmma.mma_async.sync.aligned.m64n128k16.f32.bf16.bf16 "
    "{%0, %1, %2, %3, %4, %5, %6, %7, %8, %9, %10, %11, %12, %13, %14, %15, %16, %17, %18, %19, %20, %21, %22, %23, %24, %25, %26, %27, %28, %29, %30, %31, %32, %33, %34, %35, %36, %37, %38, %39, %40, %41, %42, %43, %44, %45, %46, %47, %48, %49, %50, %51, %52, %53, %54, %55, %56, %57, %58, %59, %60, %61, %62, %63}, "
    "da, db, p, 1, 1, 0, 0;\n"
    "add.u32 la, %64, 2;\nadd.u32 lb, %65, 2;\nmov.b64 da, {la, hi};\nmov.b64 db, {lb, hi};\n"
    "wgmma.mma_async.sync.aligned.m64n128k16.f32.bf16.bf16 "
    "{%0, %1, %2, %3, %4, %5, %6, %7, %8, %9, %10, %11, %12, %13, %14, %15, %16, %17, %18, %19, %20, %21, %22, %23, %24, %25, %26, %27, %28, %29, %30, %31, %32, %33, %34, %35, %36, %37, %38, %39, %40, %41, %42, %43, %44, %45, %46, %47, %48, %49, %50, %51, %52, %53, %54, %55, %56, %57, %58, %59, %60, %61, %62, %63}, "
    "da, db, 1, 1, 1, 0, 0;\n"
    "add.u32 la, %64, 4;\nadd.u32 lb, %65, 4;\nmov.b64 da, {la, hi};\nmov.b64 db, {lb, hi};\n"
    "wgmma.mma_async.sync.aligned.m64n128k16.f32.bf16.bf16 "
    "{%0, %1, %2, %3, %4, %5, %6, %7, %8, %9, %10, %11, %12, %13, %14, %15, %16, %17, %18, %19, %20, %21, %22, %23, %24, %25, %26, %27, %28, %29, %30, %31, %32, %33, %34, %35, %36, %37, %38, %39, %40, %41, %42, %43, %44, %45, %46, %47, %48, %49, %50, %51, %52, %53, %54, %55, %56, %57, %58, %59, %60, %61, %62, %63}, "
    "da, db, 1, 1, 1, 0, 0;\n"
    "add.u32 la, %64, 6;\nadd.u32 lb, %65, 6;\nmov.b64 da, {la, hi};\nmov.b64 db, {lb, hi};\n"
    "wgmma.mma_async.sync.aligned.m64n128k16.f32.bf16.bf16 "
    "{%0, %1, %2, %3, %4, %5, %6, %7, %8, %9, %10, %11, %12, %13, %14, %15, %16, %17, %18, %19, %20, %21, %22, %23, %24, %25, %26, %27, %28, %29, %30, %31, %32, %33, %34, %35, %36, %37, %38, %39, %40, %41, %42, %43, %44, %45, %46, %47, %48, %49, %50, %51, %52, %53, %54, %55, %56, %57, %58, %59, %60, %61, %62, %63}, "
    "da, db, 1, 1, 1, 0, 0;\n"
    "}\n"
    : "+f"(d[0]), "+f"(d[1]), "+f"(d[2]), "+f"(d[3]), "+f"(d[4]), "+f"(d[5]), "+f"(d[6]), "+f"(d[7]), "+f"(d[8]), "+f"(d[9]), "+f"(d[10]), "+f"(d[11]), "+f"(d[12]), "+f"(d[13]), "+f"(d[14]), "+f"(d[15]), "+f"(d[16]), "+f"(d[17]), "+f"(d[18]), "+f"(d[19]), "+f"(d[20]), "+f"(d[21]), "+f"(d[22]), "+f"(d[23]), "+f"(d[24]), "+f"(d[25]), "+f"(d[26]), "+f"(d[27]), "+f"(d[28]), "+f"(d[29]), "+f"(d[30]), "+f"(d[31]), "+f"(d[32]), "+f"(d[33]), "+f"(d[34]), "+f"(d[35]), "+f"(d[36]), "+f"(d[37]), "+f"(d[38]), "+f"(d[39]), "+f"(d[40]), "+f"(d[41]), "+f"(d[42]), "+f"(d[43]), "+f"(d[44]), "+f"(d[45]), "+f"(d[46]), "+f"(d[47]), "+f"(d[48]), "+f"(d[49]), "+f"(d[50]), "+f"(d[51]), "+f"(d[52]), "+f"(d[53]), "+f"(d[54]), "+f"(d[55]), "+f"(d[56]), "+f"(d[57]), "+f"(d[58]), "+f"(d[59]), "+f"(d[60]), "+f"(d[61]), "+f"(d[62]), "+f"(d[63])
    : "r"(a), "r"(b), "r"(scale_d));
}
__device__ __forceinline__ void wgmma4_n128_tb1(float (&d)[64], uint32_t a, uint32_t b, int scale_d) {
  asm volatile("{\n.reg .pred p;\n.reg .b32 la, lb, hi;\n.reg .b64 da, db;\nsetp.ne.b32 p, %66, 0;\nmov.b32 hi, 0x40000040;\n"
    "add.u32 la, %64, 0;\nadd.u32 lb, %65, 0;\nmov.b64 da, {la, hi};\nmov.b64 db, {lb, hi};\n"
    "wgmma.mma_async.sync.aligned.m64n128k16.f32.bf16.bf16 "
    "{%0, %1, %2, %3, %4, %5, %6, %7, %8, %9, %10, %11, %12, %13, %14, %15, %16, %17, %18, %19, %20, %21, %22, %23, %24, %25, %26, %27, %28, %29, %30, %31, %32, %33, %34, %35, %36, %37, %38, %39, %40, %41, %42, %43, %44, %45, %46, %47, %48, %49, %50, %51, %52, %53, %54, %55, %56, %57, %58, %59, %60, %61, %62, %63}, "
    "da, db, p, 1, 1, 0, 1;\n"
    "add.u32 la, %64, 2;\nadd.u32 lb, %65, 128;\nmov.b64 da, {la, hi};\nmov.b64 db, {lb, hi};\n"
    "wgmma.mma_async.sync.aligned.m64n128k16.f32.bf16.bf16 "
    "{%0, %1, %2, %3, %4, %5, %6, %7, %8, %9, %10, %11, %12, %13, %14, %15, %16, %17, %18, %19, %20, %21, %22, %23, %24, %25, %26, %27, %28, %29, %30, %31, %32, %33, %34, %35, %36, %37, %38, %39, %40, %41, %42, %43, %44, %45, %46, %47, %48, %49, %50, %51, %52, %53, %54, %55, %56, %57, %58, %59, %60, %61, %62, %63}, "
    "da, db, 1, 1, 1, 0, 1;\n"
    "add.u32 la, %64, 4;\nadd.u32 lb, %65, 256;\nmov.b64 da, {la, hi};\nmov.b64 db, {lb, hi};\n"
    "wgmma.mma_async.sync.aligned.m64n128k16.f32.bf16.bf16 "
    "{%0, %1, %2, %3, %4, %5, %6, %7, %8, %9, %10, %11, %12, %13, %14, %15, %16, %17, %18, %19, %20, %21, %22, %23, %24, %25, %26, %27, %28, %29, %30, %31, %32, %33, %34, %35, %36, %37, %38, %39, %40, %41, %42, %43, %44, %45, %46, %47, %48, %49, %50, %51, %52, %53, %54, %55, %56, %57, %58, %59, %60, %61, %62, %63}, "
    "da, db, 1, 1, 1, 0, 1;\n"
    "add.u32 la, %64, 6;\nadd.u32 lb, %65, 384;\nmov.b64 da, {la, hi};\nmov.b64 db, {lb, hi};\n"
    "wgmma.mma_async.sync.aligned.m64n128k16.f32.bf16.bf16 "
    "{%0, %1, %2, %3, %4, %5, %6, %7, %8, %9, %10, %11, %12, %13, %14, %15, %16, %17, %18, %19, %20, %21, %22, %23, %24, %25, %26, %27, %28, %29, %30, %31, %32, %33, %34, %35, %36, %37, %38, %39, %40, %41, %42, %43, %44, %45, %46, %47, %48, %49, %50, %51, %52, %53, %54, %55, %56, %57, %58, %59, %60, %61, %62, %63}, "
    "da, db, 1, 1, 1, 0, 1;\n"
    "}\n"
    : "+f"(d[0]), "+f"(d[1]), "+f"(d[2]), "+f"(d[3]), "+f"(d[4]), "+f"(d[5]), "+f"(d[6]), "+f"(d[7]), "+f"(d[8]), "+f"(d[9]), "+f"(d[10]), "+f"(d[11]), "+f"(d[12]), "+f"(d[13]), "+f"(d[14]), "+f"(d[15]), "+f"(d[16]), "+f"(d[17]), "+f"(d[18]), "+f"(d[19]), "+f"(d[20]), "+f"(d[21]), "+f"(d[22]), "+f"(d[23]), "+f"(d[24]), "+f"(d[25]), "+f"(d[26]), "+f"(d[27]), "+f"(d[28]), "+f"(d[29]), "+f"(d[30]), "+f"(d[31]), "+f"(d[32]), "+f"(d[33]), "+f"(d[34]), "+f"(d[35]), "+f"(d[36]), "+f"(d[37]), "+f"(d[38]), "+f"(d[39]), "+f"(d[40]), "+f"(d[41]), "+f"(d[42]), "+f"(d[43]), "+f"(d[44]), "+f"(d[45]), "+f"(d[46]), "+f"(d[47]), "+f"(d[48]), "+f"(d[49]), "+f"(d[50]), "+f"(d[51]), "+f"(d[52]), "+f"(d[53]), "+f"(d[54]), "+f"(d[55]), "+f"(d[56]), "+f"(d[57]), "+f"(d[58]), "+f"(d[59]), "+f"(d[60]), "+f"(d[61]), "+f"(d[62]), "+f"(d[63])
    : "r"(a), "r"(b), "r"(scale_d));
}
__device__ __forceinline__ void wgmma4_n96_tb1(float (&d)[48], uint32_t a, uint32_t b, int scale_d) {
  asm volatile("{\n.reg .pred p;\n.reg .b32 la, lb, hi;\n.reg .b64 da, db;\nsetp.ne.b32 p, %50, 0;\nmov.b32 hi, 0x40000040;\n"
    "add.u32 la, %48, 0;\nadd.u32 lb, %49, 0;\nmov.b64 da, {la, hi};\nmov.b64 db, {lb, hi};\n"
    "wgmma.mma_async.sync.aligned.m64n96k16.f32.bf16.bf16 "
    "{%0, %1, %2, %3, %4, %5, %6, %7, %8, %9, %10, %11, %12, %13, %14, %15, %16, %17, %18, %19, %20, %21, %22, %23, %24, %25, %26, %27, %28, %29, %30, %31, %32, %33, %34, %35, %36, %37, %38, %39, %40, %41, %42, %43, %44, %45, %46, %47}, "
    "da, db, p, 1, 1, 0, 1;\n"
    "add.u32 la, %48, 2;\nadd.u32 lb, %49, 128;\nmov.b64 da, {la, hi};\nmov.b64 db, {lb, hi};\n"
    "wgmma.mma_async.sync.aligned.m64n96k16.f32.bf16.bf16 "
    "{%0, %1, %2, %3, %4, %5, %6, %7, %8, %9, %10, %11, %12, %13, %14, %15, %16, %17, %18, %19, %20, %21, %22, %23, %24, %25, %26, %27, %28, %29, %30, %31, %32, %33, %34, %35, %36, %37, %38, %39, %40, %41, %42, %43, %44, %45, %46, %47}, "
    "da, db, 1, 1, 1, 0, 1;\n"
    "add.u32 la, %48, 4;\nadd.u32 lb, %49, 256;\nmov.b64 da, {la, hi};\nmov.b64 db, {lb, hi};\n"
    "wgmma.mma_async.sync.aligned.m64n96k16.f32.bf16.bf16 "
    "{%0, %1, %2, %3, %4, %5, %6, %7, %8, %9, %10, %11, %12, %13, %14, %15, %16, %17, %18, %19, %20, %21, %22, %23, %24, %25, %26, %27, %28, %29, %30, %31, %32, %33, %34, %35, %36, %37, %38, %39, %40, %41, %42, %43, %44, %45, %46, %47}, "
    "da, db, 1, 1, 1, 0, 1;\n"
    "add.u32 la, %48, 6;\nadd.u32 lb, %49, 384;\nmov.b64 da, {la, hi};\nmov.b64 db, {lb, hi};\n"
    "wgmma.mma_async.sync.aligned.m64n96k16.f32.bf16.bf16 "
    "{%0, %1, %2, %3, %4, %5, %6, %7, %8, %9, %10, %11, %12, %13, %14, %15, %16, %17, %18, %19, %20, %21, %22, %23, %24, %25, %26, %27, %28, %29, %30, %31, %32, %33, %34, %35, %36, %37, %38, %39, %40, %41, %42, %43, %44, %45, %46, %47}, "
    "da, db, 1, 1, 1, 0, 1;\n"
    "}\n"
    : "+f"(d[0]), "+f"(d[1]), "+f"(d[2]), "+f"(d[3]), "+f"(d[4]), "+f"(d[5]), "+f"(d[6]), "+f"(d[7]), "+f"(d[8]), "+f"(d[9]), "+f"(d[10]), "+f"(d[11]), "+f"(d[12]), "+f"(d[13]), "+f"(d[14]), "+f"(d[15]), "+f"(d[16]), "+f"(d[17]), "+f"(d[18]), "+f"(d[19]), "+f"(d[20]), "+f"(d[21]), "+f"(d[22]), "+f"(d[23]), "+f"(d[24]), "+f"(d[25]), "+f"(d[26]), "+f"(d[27]), "+f"(d[28]), "+f"(d[29]), "+f"(d[30]), "+f"(d[31]), "+f"(d[32]), "+f"(d[33]), "+f"(d[34]), "+f"(d[35]), "+f"(d[36]), "+f"(d[37]), "+f"(d[38]), "+f"(d[39]), "+f"(d[40]), "+f"(d[41]), "+f"(d[42]), "+f"(d[43]), "+f"(d[44]), "+f"(d[45]), "+f"(d[46]), "+f"(d[47])
    : "r"(a), "r"(b), "r"(scale_d));
}

__device__ __forceinline__ void bar_arrive(int id, int n) { asm volatile("bar.arrive %0, %1;" :: "r"(id), "r"(n) : "memory"); }
__device__ __forceinline__ void bar_sync(int id, int n) { asm volatile("bar.sync %0, %1;" :: "r"(id), "r"(n) : "memory"); }
__device__ __forceinline__ unsigned ld_rlx(const unsigned* p) { unsigned v; asm volatile("ld.relaxed.gpu.global.u32 %0, [%1];" : "=r"(v) : "l"(p) : "memory"); return v; }
__device__ __forceinline__ void red_add(unsigned* p) { asm volatile("red.relaxed.gpu.global.add.u32 [%0], 1;" :: "l"(p) : "memory"); }
__device__ __forceinline__ void wait_cnt(const unsigned* p, unsigned target) {
  for (uint32_t n = 0; n < (1u << 14); n++) if ((int)(ld_rlx(p) - target) >= 0) break;
}
__device__ __forceinline__ float bf_lo(uint32_t v) { return __uint_as_float(v << 16); }
__device__ __forceinline__ float bf_hi(uint32_t v) { return __uint_as_float(v & 0xffff0000u); }
__device__ __forceinline__ uint32_t pack2(float lo, float hi) { uint32_t r; asm("cvt.rn.bf16x2.f32 %0, %1, %2;" : "=r"(r) : "f"(hi), "f"(lo)); return r; }
__device__ __forceinline__ uint32_t pack2v(float lo, float hi) { uint32_t r; asm volatile("cvt.rn.bf16x2.f32 %0, %1, %2;" : "=r"(r) : "f"(hi), "f"(lo)); return r; }
__device__ __forceinline__ float bfr(float v) { return bf_hi(pack2(0.f, v)); }
__device__ __forceinline__ uint32_t tagf(float v, uint32_t tag) { return (__float_as_uint(v) & ~3u) | tag; }
template <int OFF> __device__ __forceinline__ uint4 ld_msg(const void* p) { uint4 v; asm volatile("ld.relaxed.gpu.global.v4.u32 {%0,%1,%2,%3}, [%4 + %5];" : "=r"(v.x), "=r"(v.y), "=r"(v.z), "=r"(v.w) : "l"(p), "n"(OFF) : "memory"); return v; }
__device__ __forceinline__ void st_msg(void* p, uint32_t a, uint32_t b, uint32_t c, uint32_t d) { asm volatile("st.relaxed.gpu.global.v4.u32 [%0], {%1,%2,%3,%4};" :: "l"(p), "r"(a), "r"(b), "r"(c), "r"(d) : "memory"); }
__device__ __forceinline__ uint32_t stale(const uint4& v, uint32_t tag) { return ((v.x ^ tag) | (v.y ^ tag) | (v.z ^ tag) | (v.w ^ tag)) & 3u; }
__device__ __forceinline__ void sts4(uint32_t a, uint32_t x, uint32_t y, uint32_t z, uint32_t w) { asm volatile("st.shared.v4.u32 [%0], {%1,%2,%3,%4};" :: "r"(a), "r"(x), "r"(y), "r"(z), "r"(w) : "memory"); }
__device__ __forceinline__ void tma_st2d(const CUtensorMap* m, uint32_t src, int c0, int c1) {
  asm volatile("cp.async.bulk.tensor.2d.global.shared::cta.bulk_group [%0, {%2, %3}], [%1];" :: "l"(m), "r"(src), "r"(c0), "r"(c1) : "memory");
}
__device__ __forceinline__ void tma_st3d(const CUtensorMap* m, uint32_t src, int c0, int c1, int c2) {
  asm volatile("cp.async.bulk.tensor.3d.global.shared::cta.bulk_group [%0, {%2, %3, %4}], [%1];" :: "l"(m), "r"(src), "r"(c0), "r"(c1), "r"(c2) : "memory");
}
__device__ __forceinline__ float rcp_f(float v) { float r; asm("rcp.approx.f32 %0, %1;" : "=f"(r) : "f"(v)); return r; }
__device__ __forceinline__ float sqrt_f(float v) { float r; asm("sqrt.approx.f32 %0, %1;" : "=f"(r) : "f"(v)); return r; }
__device__ __forceinline__ float tanh_f(float v) { float r; asm("tanh.approx.f32 %0, %1;" : "=f"(r) : "f"(v)); return r; }
__device__ __forceinline__ float gelu_half(float hf) {
  const float k0 = 2.0f * 0.7978845608028654f, k1 = 8.0f * 0.7978845608028654f * 0.044715f;
  return fmaf(hf, tanh_f(hf * fmaf(hf * hf, k1, k0)), hf);
}
__device__ __forceinline__ uint2 ld_msg2(const void* p) { uint2 v; asm volatile("ld.relaxed.gpu.global.v2.u32 {%0,%1}, [%2];" : "=r"(v.x), "=r"(v.y) : "l"(p) : "memory"); return v; }
__device__ __forceinline__ void fence_async_smem() { asm volatile("fence.proxy.async.shared::cta;" ::: "memory"); }
template <int OFF> __device__ __forceinline__ uint4 ldg_nc(const void* p) { uint4 v; asm volatile("ld.global.nc.v4.u32 {%0,%1,%2,%3}, [%4 + %5];" : "=r"(v.x), "=r"(v.y), "=r"(v.z), "=r"(v.w) : "l"(p), "n"(OFF)); return v; }
template <int OFF> __device__ __forceinline__ uint4 ldg_ord(const void* p) { uint4 v; asm volatile("ld.global.L1::no_allocate.v4.u32 {%0,%1,%2,%3}, [%4 + %5];" : "=r"(v.x), "=r"(v.y), "=r"(v.z), "=r"(v.w) : "l"(p), "n"(OFF) : "memory"); return v; }
__device__ __forceinline__ void stg4(void* p, uint32_t a, uint32_t b, uint32_t c, uint32_t d) { asm volatile("st.global.v4.u32 [%0], {%1,%2,%3,%4};" :: "l"(p), "r"(a), "r"(b), "r"(c), "r"(d) : "memory"); }
__device__ __forceinline__ float4 lds4f(uint32_t a) { float4 v; asm volatile("ld.shared.v4.f32 {%0,%1,%2,%3}, [%4];" : "=f"(v.x), "=f"(v.y), "=f"(v.z), "=f"(v.w) : "r"(a)); return v; }
__device__ __forceinline__ uint4 lds4u(uint32_t a) { uint4 v; asm volatile("ld.shared.v4.u32 {%0,%1,%2,%3}, [%4];" : "=r"(v.x), "=r"(v.y), "=r"(v.z), "=r"(v.w) : "r"(a) : "memory"); return v; }
__device__ __forceinline__ float2 lds2f(uint32_t a) { float2 v; asm volatile("ld.shared.v2.f32 {%0,%1}, [%2];" : "=f"(v.x), "=f"(v.y) : "r"(a)); return v; }
__device__ __forceinline__ void st_async4(uint32_t raddr, uint32_t a, uint32_t b, uint32_t c, uint32_t d, uint32_t rbar) {
  asm volatile("st.async.weak.shared::cluster.mbarrier::complete_tx::bytes.v4.b32 [%0], {%1,%2,%3,%4}, [%5];"
    :: "r"(raddr), "r"(a), "r"(b), "r"(c), "r"(d), "r"(rbar) : "memory");
}

struct Ctx {
  uint32_t sm;
  uint32_t da;
  uint32_t db;
  bool lead;
  int trs;
};
template <int V> struct IC { static constexpr int value = V; };
template <int S0, int S1, class F>
__device__ __forceinline__ void static_for(F&& f) {
  if constexpr (S0 < S1) { f(IC<S0>{}); static_for<S0 + 1, S1>(f); }
}
template <int N, int TB>
__device__ __forceinline__ void mma_issue(float (&acc)[N / 2], const Ctx& c, uint32_t offa, uint32_t offb, int accum) {
  const uint32_t a = c.da + (offa >> 4), b = c.db + (offb >> 4) + (TB ? (512u << 16) : (1u << 16));
  wg_fence();
  if constexpr (N == 128 && TB == 0) wgmma4_n128_tb0(acc, a, b, accum);
  if constexpr (N == 128 && TB == 1) wgmma4_n128_tb1(acc, a, b, accum);
  if constexpr (N == 96) wgmma4_n96_tb1(acc, a, b, accum);
  wg_commit();
}
template <int N, int S>
__device__ __forceinline__ void step1(float (&acc)[N / 2], const Ctx& c) {
  if (S < 8) mbar_wait(c.sm + OFF_BAR + BAR_XF + 8 * S, 0);
  mbar_wait(c.sm + OFF_BAR + BAR_BF + 8 * (S % NB1), (S / NB1) & 1);
  if (threadIdx.x == 0) TR(S, 3);
  mma_issue<N, 1>(acc, c, xslot(S & 7), bslot(S % NB1), (S & 7) != 0);
}
template <int TB>
__device__ __forceinline__ void step2(float (&acc)[64], Ctx& c, int st, uint32_t ph, int accum) {
  mbar_wait(c.sm + OFF_BAR + BAR_FULL + 8 * st, ph);
  mma_issue<128, TB>(acc, c, st * STB, st * STB + 16384, accum);
}
__device__ __forceinline__ void release2(const Ctx& c, int st) {
  if (c.lead) mbar_arrive(c.sm + OFF_BAR + BAR_EMPTY + 8 * st);
}
template <int S>
__device__ __forceinline__ void release(const Ctx& c) {
  if constexpr (S < S_S) {
    if (c.lead) {
      if constexpr (S + NB1 < S_S) mbar_arrive(c.sm + OFF_BAR + BAR_BE + 8 * (S % NB1));
      if constexpr (S == 9) mbar_arrive(c.sm + OFF_BAR + BAR_EMPTY);
      if constexpr (S >= 11) mbar_arrive(c.sm + OFF_BAR + BAR_EMPTY + 8 * (S - 10));
    }
  } else if constexpr (S < S_END - NST) {
    release2(c, stage_of(S));
  }
}

struct HEpi { float a0, b0, a1, b1; uint32_t vec, stg, never; uint32_t w0[4], w1[4]; };
template <int G, int I, bool WAIT, int NA>
__device__ __forceinline__ void h_unit(const float (&acc)[NA], HEpi& e, const float4 v, uint32_t free_bar, uint32_t free_par, int bar_id) {
  const int r = 4 * (4 * G + I);
  e.w0[I] = pack2v(gelu_half(fmaf(e.a0, acc[r], fmaf(e.b0, v.x, v.z))), gelu_half(fmaf(e.a0, acc[r + 1], fmaf(e.b0, v.y, v.w))));
  e.w1[I] = pack2v(gelu_half(fmaf(e.a1, acc[r + 2], fmaf(e.b1, v.x, v.z))), gelu_half(fmaf(e.a1, acc[r + 3], fmaf(e.b1, v.y, v.w))));
  if (I < 3)
    asm volatile("{\n.reg .pred p;\nsetp.ne.u32 p, %0, 0;\n@p st.shared.v2.u32 [%1], {%2, %3};\n}" :: "r"(e.never), "r"(e.stg), "r"(e.w0[I]), "r"(e.w1[I]) : "memory");
  if (I == 3) {
    if (WAIT) mbar_wait(free_bar, free_par);
    sts4(e.stg + G * 8192, e.w0[0], e.w0[1], e.w0[2], e.w0[3]);
    sts4(e.stg + G * 8192 + 512, e.w1[0], e.w1[1], e.w1[2], e.w1[3]);
    fence_async_smem();
    bar_arrive(bar_id, 288);
  }
}

__global__ void __cluster_dims__(2, 1, 1) __launch_bounds__(384, 1) fused_kernel(const __grid_constant__ Params p) {
  extern __shared__ __align__(1024) uint8_t smem_raw[];
  const uint32_t sm = (uint32_t)__cvta_generic_to_shared(smem_raw);
  const int tid = threadIdx.x, lane = tid & 31;
  const int warp = __shfl_sync(0xffffffffu, tid >> 5, 0);
  int lc;
  {
    const int c = blockIdx.x >> 1;
    if (c < 4) lc = 4 + c;
    else if (c < 36) lc = ((c - 4) & 7) * 8 + ((c - 4) >> 3);
    else lc = (1 + (c - 36) % 7) * 8 + 4 + (c - 36) / 7;
  }
  int gpc;
  { unsigned smid; asm("mov.u32 %0, %%smid;" : "=r"(smid)); const int t = smid >> 1; gpc = t < 32 ? t & 7 : t < 60 ? 1 + (t - 32) % 7 : t < 62 ? t - 54 : 0; }
  const int rk = blockIdx.x & 1, cb = lc & 3, rb = lc >> 2, j = cb * 2 + rk;
  const int row0 = rb * 128;
  const uint32_t bars = sm + OFF_BAR;
  TLC(0);
#define EPOCH() mbar_wait(bars + BAR_E, 0); unsigned epoch; asm volatile("ld.shared.u32 %0, [%1];" : "=r"(epoch) : "r"(bars + OFF_EPOCH) : "memory"); const uint32_t tag = epoch & 3
  if (warp >= 8) {
    asm volatile("setmaxnreg.dec.sync.aligned.u32 88;");
    if (warp == 8) {
      if (elect_one()) {
        for (int s = 0; s < 8; s++) mbar_init(bars + BAR_XF + 8 * s, 1);
        for (int s = 0; s < NB1; s++) { mbar_init(bars + BAR_BF + 8 * s, 1); mbar_init(bars + BAR_BE + 8 * s, 8); }
        mbar_init(bars + BAR_X16, 1);
        fence_async_smem();
        for (int k = 0; k < 8; k++) {
          mbar_expect_tx(bars + BAR_XF + 8 * k, 16384);
          tma2d(sm + xslot(k), &p.mx, k * 64, row0, bars + BAR_XF + 8 * k);
          if (k < NB1) {
            mbar_expect_tx(bars + BAR_BF + 8 * k, 16384);
            tma3d(sm + bslot(k), &p.mw1, j * 224 + 96, k * 64, 0, bars + BAR_BF + 8 * k);
          }
          if (k == X16_AT) {
            mbar_expect_tx(bars + BAR_X16, 16384);
            tma2d(sm + OFF_STG, &p.mx16, 0, (row0 + j * 16) * 8, bars + BAR_X16);
          }
        }
        for (int s = 0; s < NST; s++) { mbar_init(bars + BAR_FULL + 8 * s, 1); mbar_init(bars + BAR_EMPTY + 8 * s, 8); }
        mbar_init(bars + BAR_V, 2); for (int s = 0; s < 4; s++) mbar_init(bars + BAR_FREE + 8 * s, 1);
        mbar_init(bars + BAR_E, 1); mbar_init(bars + BAR_DEP, 1);
        mbar_init(bars + BAR_M, 1); mbar_init(bars + BAR_Y, 1); mbar_init(bars + BAR_OK, 8);
        asm volatile("fence.mbarrier_init.release.cluster;" ::: "memory");
        fence_async_smem();
        asm volatile("st.shared.u64 [%0], %1;\nst.shared.u32 [%2], %3;" :: "r"(bars + OFF_Z), "l"(0ull), "r"(bars + OFF_STOP), "r"(0) : "memory");
        mbar_expect_tx(bars + BAR_M, 16384);
        mbar_expect_tx(bars + BAR_Y, 16384);
      }
      __syncwarp();
      __syncthreads();
      asm volatile("barrier.cluster.arrive.relaxed.aligned;" ::: "memory");
      if (elect_one()) {
        const CUtensorMap* mc = rk ? &p.mci : &p.mcr;
        const CUtensorMap* md = rk ? &p.mdim : &p.mdre;
        asm volatile("prefetch.tensormap [%0];" :: "l"(mc) : "memory");
        asm volatile("prefetch.tensormap [%0];" :: "l"(&p.mxn) : "memory");
        asm volatile("prefetch.tensormap [%0];" :: "l"(&p.mh) : "memory");
        asm volatile("prefetch.tensormap [%0];" :: "l"(&p.mw2) : "memory");
        asm volatile("prefetch.tensormap [%0];" :: "l"(&p.muv) : "memory");
        asm volatile("prefetch.tensormap [%0];" :: "l"(md) : "memory");
        unsigned long long* pace = &g_pace[gpc * 16];
        unsigned long long nom = 0;
#define PACE(dt)
        for (int k = NB1, i = 0, par = 0; k < S_S; k++) {
          const uint32_t fb = bars + BAR_BF + 8 * i;
          mbar_wait(bars + BAR_BE + 8 * i, par);
          TR(k, 0); PACE(k - NB1 < 8 ? 512 : 384); TR(k, 1);
          mbar_expect_tx(fb, 16384);
          tma3d(sm + bslot(i), &p.mw1, j * 224 + (k < 8 ? 96 : 0), (k & 7) * 64, 0, fb);
          if (k == 10) tma_pf2d(mc, cb * 64, row0);
          if (++i == NB1) { i = 0; par ^= 1; }
        }
        int st = 0; uint32_t ph = 0;
        int trs = S_S;
#define P_ACQ(dt) mbar_wait(bars + BAR_EMPTY + 8 * st, ph); TR(trs, 0); PACE(dt); TR(trs, 1); trs++; const uint32_t fb = bars + BAR_FULL + 8 * st, sa = sm + st * STB, sb = sa + 16384; mbar_expect_tx(fb, DBG_A * 16384 + DBG_B * 16384)
#define P_ADV() if (++st == NST) { st = 0; ph ^= 1; }
        TLREC(11);
        mbar_wait(bars + BAR_DEP, 0);
        asm volatile("fence.proxy.async.global;" ::: "memory");
        TLREC(12);
        for (int k = 0; k < 32; k++) {
          P_ACQ(k < 2 ? 0 : k < 6 ? 384 : 512); if (DBG_A) tma2d(sa, mc, k * 64, row0, fb); if (DBG_B) tma3d(sb, &p.mxn, 0, k * 64, cb * 2, fb); P_ADV();
        }
        TLREC(13);
        mbar_wait(bars + BAR_DEP, 1);
        asm volatile("fence.proxy.async.global;" ::: "memory");
        TLREC(14);
        const int n0 = cb * 128 + rk * 64, n1 = cb * 128 + (rk ^ 1) * 64;
        for (int k = rk * 14; k < rk * 14 + 14; k++) {
          P_ACQ(512); if (DBG_A) tma2d(sa, &p.mh, k * 64, row0, fb); if (DBG_B) { tma5d(sb, &p.mw2, n0, 2 * k, fb); tma5d(sb + 8192, &p.mw2, n1, 2 * k, fb); } P_ADV();
        }
        TLREC(22);
        mbar_wait(bars + BAR_DEP, 0);
        asm volatile("fence.proxy.async.global;" ::: "memory");
        TLREC(23);
        red_add(&g_cnt[C_DONE]);
#pragma unroll 1
        for (int k = 0; k < 8; k++) {
          P_ACQ(512); if (DBG_A) tma2d(sa, &p.muv, k * 64, rk * SEQ + row0, fb); if (DBG_B) { tma5d(sb, md, k * 64, n0 >> 5, fb); tma5d(sb + 8192, md, k * 64, n1 >> 5, fb); } P_ADV();
        }
        asm volatile("st.volatile.shared.u32 [%0], %1;" :: "r"(bars + OFF_STOP), "r"(1) : "memory");
      }
    } else if (warp == 9) {
      unsigned done0 = 0;
      if (lane == 0) done0 = ld_rlx(&g_cnt[C_DONE]);
      __syncthreads();
      asm volatile("barrier.cluster.arrive.relaxed.aligned;" ::: "memory");
      const unsigned epoch = __shfl_sync(0xffffffffu, (done0 >> 7) + 1, 0);
      if (lane == 0) {
        asm volatile("st.shared.u32 [%0], %1;" :: "r"(bars + OFF_EPOCH), "r"(epoch) : "memory");
        mbar_arrive(bars + BAR_E);
        asm volatile("prefetch.tensormap [%0];" :: "l"(&p.sxn) : "memory");
        asm volatile("prefetch.tensormap [%0];" :: "l"(&p.sh) : "memory");
        asm volatile("prefetch.tensormap [%0];" :: "l"(&p.suv) : "memory");
      }
#pragma unroll 1
      for (int ev = 0; ev < 12; ev++) {
        bar_sync(1 + (ev & 3), 288);
        if (lane == 0) {
          const int g = ev < 5 ? ev - 1 : ev < 8 ? ev - 5 : ev - 8;
          if (ev == 0) tma_st2d(&p.sxn, sm + OFF_STG, 0, (row0 + j * 16) * 8);
          else if (ev < 8) tma_st2d(&p.sh, sm + OFF_STG + g * 8192, j * 224 + (ev < 5 ? 96 : 0) + g * 32, row0);
          else tma_st2d(&p.suv, sm + OFF_STG + g * 8192, cb * 128 + g * 32, rk * SEQ + row0);
          asm volatile("cp.async.bulk.commit_group;\ncp.async.bulk.wait_group.read 0;" ::: "memory");
          if (ev == 0) { mbar_arrive(bars + BAR_FREE); mbar_arrive(bars + BAR_FREE + 8); }
          else mbar_arrive(bars + BAR_FREE + 8 * g);
          if (ev == 0 || ev == 7 || ev == 11) {
            TLREC(24 + (ev >> 2));
            asm volatile("cp.async.bulk.wait_group 0;" ::: "memory");
            asm volatile("st.relaxed.gpu.global.u32 [%0], %1;" :: "l"(&g_cnt[ev == 0 ? C_XN + rb * 8 + j : (ev == 11 ? C_UV : C_H) + rb * 32 + j]), "r"(epoch) : "memory");
            TLREC(16 + (ev >> 2));
          }
        }
        __syncwarp();
        if (ev == 0 || ev == 7 || ev == 11) {
          const unsigned* f = &g_cnt[ev == 0 ? C_XN + lane * 4 : (ev == 11 ? C_UV : C_H) + rb * 32 + (lane & 1) * 4];
          for (uint32_t n = 0; n < (1u << 14); n++) {
            const uint4 v = ld_msg<0>(f);
            if (__all_sync(0xffffffffu, v.x == epoch && v.y == epoch && v.z == epoch && v.w == epoch)) break;
          }
          if (lane == 0) mbar_arrive(bars + BAR_DEP);
        }
      }
    } else {
      const int cl = lane < 28 ? lane : 27;
      const __nv_bfloat16* w = p.w1 + (size_t)(rb * 32 + (warp - 10) * 16) * FF + j * 224 + cl * 8;
      __syncthreads();
      asm volatile("barrier.cluster.arrive.relaxed.aligned;" ::: "memory");
      {
        const char* pw = reinterpret_cast<const char*>(p.w1 + (size_t)(rb * 32 + (warp - 10) * 16 + (lane >> 2)) * FF + j * 224) + ((lane & 3) == 3 ? 440 : (lane & 3) * 128);
        asm volatile("prefetch.global.L2 [%0];" :: "l"(pw)); asm volatile("prefetch.global.L2 [%0];" :: "l"(pw + 8 * FF * 2));
      }
      mbar_wait(bars + BAR_XF + 8 * W_DLY, 0);
      {
        uint4 v[16];
        static_for<0, 16>([&](auto I) { v[decltype(I)::value] = ldg_ord<decltype(I)::value * FF * 2>(w); });
        float s[8] = {0.f, 0.f, 0.f, 0.f, 0.f, 0.f, 0.f, 0.f};
#pragma unroll
        for (int r = 0; r < 16; r++) {
          s[0] += bf_lo(v[r].x); s[1] += bf_hi(v[r].x); s[2] += bf_lo(v[r].y); s[3] += bf_hi(v[r].y);
          s[4] += bf_lo(v[r].z); s[5] += bf_hi(v[r].z); s[6] += bf_lo(v[r].w); s[7] += bf_hi(v[r].w);
        }
        float4* s4 = reinterpret_cast<float4*>(smem_raw + OFF_VH);
        if (warp == 11 && lane < 28) { s4[lane * 2] = make_float4(s[0], s[1], s[2], s[3]); s4[lane * 2 + 1] = make_float4(s[4], s[5], s[6], s[7]); }
        bar_sync(5, 64);
        EPOCH();
        if (warp == 10 && lane < 28) {
          const float4 o0 = s4[lane * 2], o1 = s4[lane * 2 + 1];
          float* dst = &g_csw[rb * FF + j * 224 + lane * 8];
          st_msg(dst, tagf(s[0] + o0.x, tag), tagf(s[1] + o0.y, tag), tagf(s[2] + o0.z, tag), tagf(s[3] + o0.w, tag));
          st_msg(dst + 4, tagf(s[4] + o1.x, tag), tagf(s[5] + o1.y, tag), tagf(s[6] + o1.z, tag), tagf(s[7] + o1.w, tag));
          if (lane == 0) TLREC(15);
        }
        bar_sync(5, 64);
      }
      EPOCH();
      const int q = (warp - 10) * 28 + cl;
      const uint2 bb = *reinterpret_cast<const uint2*>(p.b1 + j * 224 + q * 4);
      if (warp == 11) {
        const uint32_t b2v = *reinterpret_cast<const uint32_t*>(p.b2 + cb * 128 + rk * 64 + lane * 2);
        *reinterpret_cast<float2*>(smem_raw + OFF_B2 + lane * 8) = make_float2(0.5f * bf_lo(b2v), 0.5f * bf_hi(b2v));
      }
      float4 acc;
      for (uint32_t n = 0; n < (1u << 14); n++) {
        const uint32_t t = ld_rlx(reinterpret_cast<const unsigned*>(&g_csw[(lane & 15) * FF + j * 224 + 223]));
        if (!__any_sync(0xffffffffu, (t ^ tag) & 3u)) break;
      }
      for (uint32_t n = 0; n < (1u << 14); n++) {
        uint32_t bad = 0;
        acc = make_float4(0.f, 0.f, 0.f, 0.f);
        uint4 m[16];
        static_for<0, 16>([&](auto I) { m[decltype(I)::value] = ld_msg<decltype(I)::value * FF * 4>(&g_csw[j * 224 + q * 4]); });
#pragma unroll
        for (int r = 0; r < 16; r++) {
          bad |= m[r].x ^ tag;
          acc.x += __uint_as_float(m[r].x); acc.y += __uint_as_float(m[r].y); acc.z += __uint_as_float(m[r].z); acc.w += __uint_as_float(m[r].w);
        }
        if (!__any_sync(0xffffffffu, bad & 3u)) break;
      }
      if (lane < 28) {
        float4* s4 = reinterpret_cast<float4*>(smem_raw + OFF_VH);
        s4[q * 2] = make_float4(acc.x, acc.y, 0.5f * bf_lo(bb.x), 0.5f * bf_hi(bb.x));
        s4[q * 2 + 1] = make_float4(acc.z, acc.w, 0.5f * bf_lo(bb.y), 0.5f * bf_hi(bb.y));
      }
      __syncwarp();
      if (lane == 0) { mbar_arrive(bars + BAR_V); if (warp == 10) TLREC(20); }
    }
  } else {
    asm volatile("setmaxnreg.inc.sync.aligned.u32 208;");
    __syncthreads();
    asm volatile("barrier.cluster.arrive.relaxed.aligned;" ::: "memory");
    Ctx c; c.sm = sm; c.lead = lane == 0; c.trs = S_S;
    c.da = (((sm + (warp >> 2) * 8192) & 0x3FFFF) >> 4) | (1u << 16); c.db = (sm & 0x3FFFF) >> 4;
    const int rl = warp * 16 + (lane >> 2);
    float Q[64], R[48], U[64], M[64], Y[64];
    HEpi e;
    e.vec = sm + OFF_VH + (lane & 3) * 16; e.stg = sm + OFF_STG + rl * 64 + (lane & 3) * 16;
    e.never = gridDim.y - 1;
    uint2 m0, m1;
    uint32_t xw[4][4];
    float mu[2], qq[2];
    static_for<0, S_ROLL>([&](auto S_) {
      constexpr int S = decltype(S_)::value;
      float4 hv[2];
      if constexpr (S > HS0) static_for<units_done(S - 1), units_done(S)>([&](auto U_) { hv[decltype(U_)::value - units_done(S - 1)] = lds4f(e.vec + hvec(decltype(U_)::value)); });
      if constexpr (S < 8) step1<128, S>(Q, c);
      else if constexpr (S < S_S) step1<96, S>(R, c);
      else step2<1>(U, c, stage_of(S), par_of(S), S > S_S);
      if (S == 0) TLC(1);
      if (S == HS0 - SLD) { m0 = ld_msg2(&g_stats[row0 + rl]); m1 = ld_msg2(&g_stats[row0 + rl + 8]); }
      if constexpr (S > 0) { wg_wait<1>(); release<S - 1>(c); }
      if (S == XS0) {
        mbar_wait(bars + BAR_X16, 0);
#pragma unroll
        for (int t = 0; t < 4; t++) {
          const int kc = (t & 1) * 4 + (lane >> 3);
          const uint4 v = lds4u(sm + OFF_STG + (warp * 2 + (t >> 1)) * 1024 + kc * 128 + (((lane & 7) ^ kc) << 4));
          xw[t][0] = v.x; xw[t][1] = v.y; xw[t][2] = v.z; xw[t][3] = v.w;
        }
      }
      if constexpr (S == XS0 || S == XS0 + 1) {
        constexpr int r = S - XS0;
        float a = bf_lo(xw[2 * r][0]), b = bf_hi(xw[2 * r][0]);
#pragma unroll
        for (int i = 1; i < 8; i++) { a += bf_lo(xw[2 * r + (i >> 2)][i & 3]); b += bf_hi(xw[2 * r + (i >> 2)][i & 3]); }
        mu[r] = a + b;
        if (r == 0) mu[0] += __shfl_xor_sync(0xffffffffu, mu[0], 16);
        else {
          mu[1] += __shfl_xor_sync(0xffffffffu, mu[1], 16);
#pragma unroll
          for (int o = 8; o > 0; o >>= 1) { mu[0] += __shfl_xor_sync(0xffffffffu, mu[0], o); mu[1] += __shfl_xor_sync(0xffffffffu, mu[1], o); }
        }
      }
      if constexpr (S == XS0 + 2 || S == XS0 + 3) {
        constexpr int r = S - XS0 - 2;
        mu[r] *= 1.0f / DM;
        const uint32_t mm = pack2(mu[r], mu[r]);
        float a = 0.f, b = 0.f;
#pragma unroll
        for (int i = 0; i < 8; i++) {
          uint32_t& w = xw[2 * r + (i >> 2)][i & 3];
          asm("sub.rn.bf16x2 %0, %0, %1;" : "+r"(w) : "r"(mm));
          a = fmaf(bf_lo(w), bf_lo(w), a); b = fmaf(bf_hi(w), bf_hi(w), b);
        }
        qq[r] = a + b;
        if (r == 0) qq[0] += __shfl_xor_sync(0xffffffffu, qq[0], 16);
        else {
          qq[1] += __shfl_xor_sync(0xffffffffu, qq[1], 16);
#pragma unroll
          for (int o = 8; o > 0; o >>= 1) { qq[0] += __shfl_xor_sync(0xffffffffu, qq[0], o); qq[1] += __shfl_xor_sync(0xffffffffu, qq[1], o); }
        }
      }
      if (S == XS0 + 4) {
        const float mean = (lane & 1) ? mu[1] : mu[0], m1 = bfr(mean), dm = mean - m1;
        const float var = fmaxf(fmaf((lane & 1) ? qq[1] : qq[0], 1.0f / DM, -dm * dm), 0.f);
        const float i1 = rcp_f(bfr(sqrt_f(bfr(bfr(var) + 1e-5f))));
        const float i2 = 0.5f * rcp_f(bfr(sqrt_f(bfr(bfr(var * i1 * i1) + 1e-5f))));
        const float rh = bfr(i1);
        const uint32_t hl = pack2(rh, i1 - rh);
        mu[0] = i1 * i2; mu[1] = -(m1 * i1 + bfr(dm * i1)) * i2;
        qq[0] = __uint_as_float(__shfl_sync(0xffffffffu, hl, 0)); qq[1] = __uint_as_float(__shfl_sync(0xffffffffu, hl, 1));
      }
      if (S == XS0 + 5) {
#pragma unroll
        for (int r = 0; r < 2; r++) {
          const uint32_t t = __float_as_uint(qq[r]), hi = __byte_perm(t, 0, 0x1010), lo = __byte_perm(t, 0, 0x3232);
#pragma unroll
          for (int i = 0; i < 8; i++) {
            uint32_t& w = xw[2 * r + (i >> 2)][i & 3];
            asm("{\n.reg .b32 t;\nmul.rn.bf16x2 t, %0, %2;\nfma.rn.bf16x2 %0, %0, %1, t;\n}" : "+r"(w) : "r"(hi), "r"(lo));
          }
        }
#pragma unroll
        for (int t = 0; t < 4; t++) {
          const int kc = (t & 1) * 4 + ((lane & 7) >> 1);
          asm volatile("stmatrix.sync.aligned.m8n8.x4.shared.b16 [%0], {%1,%2,%3,%4};"
                       :: "r"(sm + OFF_STG + (warp * 2 + (t >> 1)) * 1024 + kc * 128 + ((((lane & 1) * 4 + (lane >> 3)) ^ kc) << 4)),
                          "r"(xw[t][0]), "r"(xw[t][1]), "r"(xw[t][2]), "r"(xw[t][3]) : "memory");
        }
        fence_async_smem();
        bar_arrive(1, 288);
        TLC(28);
      }
      if (S == XS0 + 6) {
        EPOCH();
        if (lane < 2)
          asm volatile("st.relaxed.gpu.global.v2.u32 [%0], {%1,%2};" :: "l"(&g_stats[row0 + j * 16 + warp * 2 + lane]), "r"(tagf(mu[0], tag)), "r"(tagf(mu[1], tag)) : "memory");
      }
      if (S == 8) { reg_fence(Q); TLC(2); }
      if (S == S_S) { reg_fence(R); TLC(3); }
      if (S == HS0) {
        EPOCH();
        for (uint32_t n = 0; n < (1u << 14) && (((m0.x ^ tag) | (m0.y ^ tag) | (m1.x ^ tag) | (m1.y ^ tag)) & 3u); n++) {
          m0 = ld_msg2(&g_stats[row0 + rl]); m1 = ld_msg2(&g_stats[row0 + rl + 8]);
        }
        e.a0 = __uint_as_float(m0.x); e.b0 = __uint_as_float(m0.y); e.a1 = __uint_as_float(m1.x); e.b1 = __uint_as_float(m1.y);
        mbar_wait(bars + BAR_V, 0);
        TLC(21);
      }
      static_for<units_done(S - 1), units_done(S)>([&](auto U_) {
        constexpr int u = decltype(U_)::value, G = u < 16 ? u / 4 : (u - 16) / 4, ev = 1 + u / 4;
        if (S == HS0) hv[0] = lds4f(e.vec + hvec(u));
        const float4 v = hv[u - units_done(S - 1)];
        if constexpr (u < 16) h_unit<G, u % 4, (G < 2)>(Q, e, v, bars + BAR_FREE + 8 * G, 0, 1 + (ev & 3));
        else h_unit<G, u % 4, true>(R, e, v, bars + BAR_FREE + 8 * G, G < 2, 1 + (ev & 3));
      });
    });
    TLC(4);
    int st = stage_of(S_ROLL), pst = stage_of(S_ROLL - 1); uint32_t ph = par_of(S_ROLL);
#pragma unroll 1
    for (int s = S_ROLL; s < S_M; s++) {
      step2<1>(U, c, st, ph, 1);
      wg_wait<1>();
      release2(c, pst);
      pst = st; if (++st == NST) { st = 0; ph ^= 1; }
    }
    TLC(5);
    static_for<S_M, S_M + UVN>([&](auto S_) {
      constexpr int S = decltype(S_)::value;
      step2<1>(M, c, stage_of(S), par_of(S), S > S_M);
      wg_wait<1>();
      release<S - 1>(c);
      if (S == S_M) reg_fence(U);
      static_for<(S - S_M) * 4 / UVN, (S - S_M + 1) * 4 / UVN>([&](auto G_) {
        constexpr int G = decltype(G_)::value, r = 16 * G;
        mbar_wait(bars + BAR_FREE + 8 * G, G < 2 ? 0 : G == 2 ? 1 : 0);
        sts4(e.stg + G * 8192, pack2(U[r], U[r + 1]), pack2(U[r + 4], U[r + 5]), pack2(U[r + 8], U[r + 9]), pack2(U[r + 12], U[r + 13]));
        sts4(e.stg + G * 8192 + 512, pack2(U[r + 2], U[r + 3]), pack2(U[r + 6], U[r + 7]), pack2(U[r + 10], U[r + 11]), pack2(U[r + 14], U[r + 15]));
        fence_async_smem();
        bar_arrive(1 + G, 288);
      });
    });
    st = stage_of(S_M + UVN); pst = stage_of(S_M + UVN - 1); ph = par_of(S_M + UVN);
#pragma unroll 1
    for (int s = S_M + UVN; s < S_Y; s++) {
      step2<1>(M, c, st, ph, 1);
      wg_wait<1>();
      release2(c, pst);
      pst = st; if (++st == NST) { st = 0; ph ^= 1; }
    }
    TLC(6);
    const size_t ooff = (size_t)(row0 + rl) * DM + cb * 128 + rk * 64 + (lane & 3) * 8;
    const uint32_t mine = warp * 4096 + lane * 16, peer = rk ^ 1, sgn = rk ? 0x80008000u : 0u;
    uint4 g[4], xr[4];
    static_for<S_Y, S_END>([&](auto S_) {
      constexpr int S = decltype(S_)::value;
      step2<0>(Y, c, stage_of(S), par_of(S), S > S_Y);
      wg_wait<1>();
      release<S - 1>(c);
      if (S == S_Y) {
        reg_fence(M);
        asm volatile("barrier.cluster.wait.aligned;" ::: "memory");
        const uint32_t ra = mapa(sm + OFF_STG + mine, peer), rbar = mapa(bars + BAR_M, peer);
#pragma unroll
        for (int v = 0; v < 4; v++)
          st_async4(ra + v * 512, pack2(M[32 + 8 * v], M[33 + 8 * v]), pack2(M[34 + 8 * v], M[35 + 8 * v]), pack2(M[36 + 8 * v], M[37 + 8 * v]), pack2(M[38 + 8 * v], M[39 + 8 * v]), rbar);
        xr[0] = ldg_nc<0>(p.x + ooff); xr[1] = ldg_nc<16 * DM>(p.x + ooff);
        xr[2] = ldg_nc<64>(p.x + ooff); xr[3] = ldg_nc<16 * DM + 64>(p.x + ooff);
      }
      if (S == S_Y + 3) {
        mbar_wait(bars + BAR_M, 0);
#pragma unroll
        for (int v = 0; v < 4; v++) {
          const uint4 t = lds4u(sm + OFF_STG + mine + v * 512);
          M[8 * v] += bf_lo(t.x); M[8 * v + 1] += bf_hi(t.x); M[8 * v + 2] += bf_lo(t.y); M[8 * v + 3] += bf_hi(t.y);
          M[8 * v + 4] += bf_lo(t.z); M[8 * v + 5] += bf_hi(t.z); M[8 * v + 6] += bf_lo(t.w); M[8 * v + 7] += bf_hi(t.w);
        }
      }
      if (S == S_END - NST + 1 && c.lead) mbar_arrive_cluster(mapa(bars + BAR_OK, peer));
      if constexpr (S >= S_Y + 4) {
        constexpr int G = (S - S_Y - 4) >> 1, H = (S - S_Y - 4) & 1;
        uint32_t w[4];
#pragma unroll
        for (int i = 0; i < 4; i++) {
          const float2 b = lds2f(sm + OFF_B2 + (32 * G + 8 * i) * 4 + (lane & 3) * 8);
          const int r = 4 * (4 * G + i) + 2 * H;
          const float z0 = fmaf(M[r], 0.5f, b.x), z1 = fmaf(M[r + 1], 0.5f, b.y);
          w[i] = pack2(fmaf(z0, tanh_f(z0), z0), fmaf(z1, tanh_f(z1), z1)) ^ sgn;
        }
        const uint32_t tb = sm + OFF_STG + warp * 4096 + (2 * G + H) * 512;
        __syncwarp();
        asm volatile("stmatrix.sync.aligned.m8n8.x4.shared.b16 [%0], {%1,%2,%3,%4};"
                     :: "r"(tb + (lane & 7) * 64 + (((lane >> 3) ^ ((lane >> 1) & 3)) << 4)), "r"(w[0]), "r"(w[1]), "r"(w[2]), "r"(w[3]) : "memory");
        __syncwarp();
        g[2 * G + H] = lds4u(tb + (lane >> 2) * 64 + (((lane & 3) ^ ((lane >> 3) & 3)) << 4));
      }
    });
    mbar_wait(bars + BAR_OK, 0);
    const uint32_t rl_ = mapa(sm + LAND_STAGE * STB + mine, peer), rlb = mapa(bars + BAR_Y, peer);
    TLC(7);
    wg_wait<0>();
    reg_fence(Y);
    TLC(8);
#pragma unroll
    for (int v = 0; v < 4; v++)
      st_async4(rl_ + v * 512, pack2(Y[32 + 8 * v], Y[33 + 8 * v]), pack2(Y[34 + 8 * v], Y[35 + 8 * v]), pack2(Y[36 + 8 * v], Y[37 + 8 * v]), pack2(Y[38 + 8 * v], Y[39 + 8 * v]), rlb);
    mbar_wait(bars + BAR_Y, 0);
    TLC(9);
#pragma unroll
    for (int G = 0; G < 2; G++) {
      uint32_t o0[4], o1[4];
      const uint4 tv[2] = {lds4u(sm + LAND_STAGE * STB + mine + 2 * G * 512), lds4u(sm + LAND_STAGE * STB + mine + (2 * G + 1) * 512)};
      const uint32_t g0[4] = {g[2 * G].x, g[2 * G].y, g[2 * G].z, g[2 * G].w}, g1[4] = {g[2 * G + 1].x, g[2 * G + 1].y, g[2 * G + 1].z, g[2 * G + 1].w};
      const uint32_t x0[4] = {xr[2 * G].x, xr[2 * G].y, xr[2 * G].z, xr[2 * G].w}, x1[4] = {xr[2 * G + 1].x, xr[2 * G + 1].y, xr[2 * G + 1].z, xr[2 * G + 1].w};
#pragma unroll
      for (int i = 0; i < 4; i++) {
        const int a = 4 * (4 * G + i);
        const uint32_t t0 = (i & 1) ? tv[i >> 1].z : tv[i >> 1].x, t1 = (i & 1) ? tv[i >> 1].w : tv[i >> 1].y;
        o0[i] = pack2(fmaf(Y[a] - bf_lo(t0), bf_lo(g0[i]), bf_lo(x0[i])), fmaf(Y[a + 1] - bf_hi(t0), bf_hi(g0[i]), bf_hi(x0[i])));
        o1[i] = pack2(fmaf(Y[a + 2] - bf_lo(t1), bf_lo(g1[i]), bf_lo(x1[i])), fmaf(Y[a + 3] - bf_hi(t1), bf_hi(g1[i]), bf_hi(x1[i])));
      }
      stg4(p.out + ooff + 32 * G, o0[0], o0[1], o0[2], o0[3]);
      stg4(p.out + ooff + 32 * G + 8 * DM, o1[0], o1[1], o1[2], o1[3]);
    }
    TLC(10);
  }
}

typedef CUresult (*EncFn)(CUtensorMap*, CUtensorMapDataType, cuuint32_t, void*, const cuuint64_t*, const cuuint64_t*, const cuuint32_t*,
                          const cuuint32_t*, CUtensorMapInterleave, CUtensorMapSwizzle, CUtensorMapL2promotion, CUtensorMapFloatOOBfill);

void make_map(EncFn enc, CUtensorMap* m, const void* ptr, int nd, const uint64_t* dims, const uint64_t* strides, const uint32_t* box,
              CUtensorMapSwizzle sw = CU_TENSOR_MAP_SWIZZLE_128B) {
  const cuuint32_t es[5] = {1, 1, 1, 1, 1};
  cuuint64_t d[5], s[5]; cuuint32_t b[5];
  for (int i = 0; i < nd; i++) { d[i] = dims[i]; b[i] = box[i]; if (i + 1 < nd) s[i] = strides[i]; }
  enc(m, CU_TENSOR_MAP_DATA_TYPE_BFLOAT16, nd, const_cast<void*>(ptr), d, s, b, es, CU_TENSOR_MAP_INTERLEAVE_NONE,
      sw, CU_TENSOR_MAP_L2_PROMOTION_L2_128B, CU_TENSOR_MAP_FLOAT_OOB_FILL_NONE);
}

}

extern "C" void kernel_launch(void* const* d_in, const int* in_sizes, int n_in, void* d_out, int out_size) {
  static Params prm;
  static const void* key[11];
  static EncFn enc = nullptr;
  bool same = enc != nullptr && key[10] == d_out;
  for (int i = 0; i < 10 && same; i++) same = key[i] == d_in[i];
  if (!same) {
    if (!enc) {
      cudaDriverEntryPointQueryResult q;
      cudaGetDriverEntryPoint("cuTensorMapEncodeTiled", reinterpret_cast<void**>(&enc), cudaEnableDefault, &q);
      cudaFuncSetAttribute(fused_kernel, cudaFuncAttributeMaxDynamicSharedMemorySize, SMEM_BYTES);
    }
    void *xn, *uv, *h;
    cudaGetSymbolAddress(&xn, g_xn);
    cudaGetSymbolAddress(&uv, g_uv);
    cudaGetSymbolAddress(&h, g_h);
    const uint64_t R = DM * 2;
    const uint32_t box2[2] = {64, 128}, box3[3] = {64, 64, 2}, box5[5] = {64, 2, 4, 4, 2}, boxs[2] = {32, 128};
    { const uint64_t d[2] = {DM, SEQ}, s[1] = {R}; make_map(enc, &prm.mx, d_in[0], 2, d, s, box2); }
    { const uint64_t d[2] = {64, SEQ * 8}, s[1] = {128}; make_map(enc, &prm.mx16, d_in[0], 2, d, s, box2); make_map(enc, &prm.sxn, xn, 2, d, s, box2); }
    { const uint64_t d[3] = {64, SEQ, 8}, s[2] = {R, 128}; make_map(enc, &prm.mxn, xn, 3, d, s, box3); }
    { const uint64_t d[2] = {SEQ, SEQ}, s[1] = {SEQ * 2}; make_map(enc, &prm.mcr, d_in[1], 2, d, s, box2); make_map(enc, &prm.mci, d_in[2], 2, d, s, box2); }
    { const uint64_t d[5] = {DM, 2, 4, 4, DM / 32}, s[4] = {R, 8 * R, 2 * R, 32 * R};
      make_map(enc, &prm.mdre, d_in[3], 5, d, s, box5); make_map(enc, &prm.mdim, d_in[4], 5, d, s, box5); }
    { const uint64_t d[3] = {FF, DM, 2}, s[2] = {FF * 2, 128}; make_map(enc, &prm.mw1, d_in[6], 3, d, s, box3); }
    { const uint64_t d[2] = {FF, SEQ}, s[1] = {FF * 2}; make_map(enc, &prm.mh, h, 2, d, s, box2); make_map(enc, &prm.sh, h, 2, d, s, boxs, CU_TENSOR_MAP_SWIZZLE_NONE); }
    { const uint64_t d[5] = {DM, 2, 4, 4, FF / 32}, s[4] = {R, 8 * R, 2 * R, 32 * R}; make_map(enc, &prm.mw2, d_in[8], 5, d, s, box5); }
    { const uint64_t d[2] = {DM, 2 * SEQ}, s[1] = {R}; make_map(enc, &prm.muv, uv, 2, d, s, box2); make_map(enc, &prm.suv, uv, 2, d, s, boxs, CU_TENSOR_MAP_SWIZZLE_NONE); }
    prm.x = (const __nv_bfloat16*)d_in[0]; prm.w1 = (const __nv_bfloat16*)d_in[6]; prm.b1 = (const __nv_bfloat16*)d_in[7];
    prm.cr = (const __nv_bfloat16*)d_in[1]; prm.ci = (const __nv_bfloat16*)d_in[2]; prm.dre = (const __nv_bfloat16*)d_in[3];
    prm.dim = (const __nv_bfloat16*)d_in[4]; prm.w2 = (const __nv_bfloat16*)d_in[8];
    prm.b2 = (const __nv_bfloat16*)d_in[9]; prm.out = (__nv_bfloat16*)d_out;
    for (int i = 0; i < 10; i++) key[i] = d_in[i];
    key[10] = d_out;
  }
  fused_kernel<<<128, 384, SMEM_BYTES>>>(prm);
}
```

```cpp
#include <cuda_runtime.h>
#include <cuda_bf16.h>
#include <cuda.h>
#include <stdint.h>

namespace {

constexpr int SEQ = 2048, DM = 512, FF = 1792;
constexpr int NST = 6;
constexpr int STB = 32768;
constexpr int OFF_STG = NST * STB;
constexpr int OFF_VH = OFF_STG + 32768;
constexpr int OFF_B2 = OFF_VH + 1792;
constexpr int OFF_BAR = OFF_B2 + 256;
constexpr int SMEM_BYTES = OFF_BAR + 376;
static_assert(SMEM_BYTES <= 232448, "smem");
constexpr int BAR_FULL = 0, BAR_EMPTY = 48, BAR_XF = 96, BAR_BF = 160, BAR_BE = 336, BAR_X16 = 224, BAR_V = 232, BAR_FREE = 304,
              BAR_E = 248, BAR_M = 256, BAR_Y = 264, BAR_OK = 272, BAR_DEP = 280, OFF_EPOCH = 288, OFF_STOP = 292, OFF_Z = 296;
__host__ __device__ constexpr int xslot(int k) { return (k < 4 ? k : 2 * k - 4) * 16384; }
constexpr int NB1 = 5;
__host__ __device__ constexpr int bslot(int i) { return i == 0 ? 11 * 16384 : i == 4 ? OFF_STG + 16384 : (3 + 2 * i) * 16384; }
constexpr int S_S = 16, S_M = 48, S_Y = 62, S_END = 70;
__host__ __device__ constexpr int stage_of(int s) { return (s - S_S) % NST; }
__host__ __device__ constexpr int par_of(int s) { return ((s - S_S) / NST) & 1; }
constexpr int LAND_STAGE = stage_of(S_END - NST);
#define X16_AT 0
#define PACE_MAX 1500
#define DBG_A 1
#define DBG_B 1
#define PF_NS 700
#define PF_W 7
#define PACE_W 11
#define UVN 4
#define W_DLY 7
#define SLD 2
#define G_DLY 11
#define XS0 0
#define HS0 13
#define UNUM 8
#define UDEN 7
__host__ __device__ constexpr int units_done(int s) {
  const int n = s < HS0 ? 0 : s < S_S ? s - HS0 + 1 : (S_S - HS0) + ((s - S_S + 1) * UNUM) / UDEN;
  return n > 28 ? 28 : n;
}
__host__ __device__ constexpr int hvec(int u) { return (u < 16 ? 48 + 4 * u : 4 * (u - 16)) * 16; }
__host__ __device__ constexpr int last_unit_step() { int s = 0; while (units_done(s) < 28) s++; return s; }
constexpr int S_ROLL = last_unit_step() + 1;

constexpr int C_DONE = 0, C_XN = 32, C_H = 64, C_UV = 64 + 16 * 32;

struct Params {
  CUtensorMap mx, mx16, sxn, mxn, mw1, mcr, mci, mh, sh, mw2, muv, suv, mdre, mdim;
  const __nv_bfloat16 *x, *w1, *b1, *b2, *cr, *ci, *dre, *dim, *w2;
  __nv_bfloat16* out;
};

__device__ __align__(1024) __nv_bfloat16 g_xn[SEQ * DM];
__device__ __align__(1024) __nv_bfloat16 g_uv[2 * SEQ * DM];
__device__ __align__(1024) __nv_bfloat16 g_h[SEQ * FF];
__device__ float2 g_stats[SEQ];
__device__ __align__(16) float g_csw[16 * FF];
__device__ __align__(128) unsigned g_cnt[160 + 32 * 32];
__device__ unsigned long long g_pace[8 * 16];
#define TR(step, k) do {} while (0)
#define TLREC(ev) do {} while (0)
#define TLC(ev) do {} while (0)

__device__ __forceinline__ void mbar_init(uint32_t bar, uint32_t cnt) { asm volatile("mbarrier.init.shared::cta.b64 [%0], %1;" :: "r"(bar), "r"(cnt) : "memory"); }
__device__ __forceinline__ void mbar_expect_tx(uint32_t bar, uint32_t bytes) { asm volatile("mbarrier.arrive.expect_tx.shared::cta.b64 _, [%0], %1;" :: "r"(bar), "r"(bytes) : "memory"); }
__device__ __forceinline__ void mbar_arrive(uint32_t bar) { asm volatile("mbarrier.arrive.shared::cta.b64 _, [%0];" :: "r"(bar) : "memory"); }
__device__ __forceinline__ void mbar_arrive_cluster(uint32_t remote_bar) { asm volatile("mbarrier.arrive.shared::cluster.b64 _, [%0];" :: "r"(remote_bar) : "memory"); }
__device__ __forceinline__ uint32_t mapa(uint32_t addr, uint32_t cta) { uint32_t r; asm("mapa.shared::cluster.u32 %0, %1, %2;" : "=r"(r) : "r"(addr), "r"(cta)); return r; }
__device__ __forceinline__ bool mbar_try(uint32_t bar, uint32_t parity) {
  uint32_t ok;
  asm volatile("{\n.reg .pred p;\nmbarrier.try_wait.parity.shared::cta.b64 p, [%1], %2;\nselp.u32 %0, 1, 0, p;\n}" : "=r"(ok) : "r"(bar), "r"(parity) : "memory");
  return ok;
}
__device__ __forceinline__ void mbar_wait(uint32_t bar, uint32_t parity) {
  if (mbar_try(bar, parity)) return;
  for (uint32_t n = 0; n < (1u << 15); n++) if (mbar_try(bar, parity)) break;
}
__device__ __forceinline__ bool elect_one() {
  uint32_t p;
  asm volatile("{\n.reg .pred p;\nelect.sync _|p, 0xffffffff;\nselp.u32 %0, 1, 0, p;\n}" : "=r"(p));
  return p;
}
__device__ __forceinline__ void tma2d(uint32_t dst, const CUtensorMap* m, int c0, int c1, uint32_t bar) {
  asm volatile("cp.async.bulk.tensor.2d.shared::cluster.global.mbarrier::complete_tx::bytes [%0], [%1, {%3, %4}], [%2];"
    :: "r"(dst), "l"(m), "r"(bar), "r"(c0), "r"(c1) : "memory");
}
__device__ __forceinline__ void tma3d(uint32_t dst, const CUtensorMap* m, int c0, int c1, int c2, uint32_t bar) {
  asm volatile("cp.async.bulk.tensor.3d.shared::cluster.global.mbarrier::complete_tx::bytes [%0], [%1, {%3, %4, %5}], [%2];"
    :: "r"(dst), "l"(m), "r"(bar), "r"(c0), "r"(c1), "r"(c2) : "memory");
}
__device__ __forceinline__ void tma5d(uint32_t dst, const CUtensorMap* m, int c0, int c4, uint32_t bar) {
  asm volatile("cp.async.bulk.tensor.5d.shared::cluster.global.mbarrier::complete_tx::bytes [%0], [%1, {%3, %5, %5, %5, %4}], [%2];"
    :: "r"(dst), "l"(m), "r"(bar), "r"(c0), "r"(c4), "r"(0) : "memory");
}
__device__ __forceinline__ void tma_pf2d(const CUtensorMap* m, int c0, int c1) {
  asm volatile("cp.async.bulk.prefetch.tensor.2d.L2.global [%0, {%1, %2}];" :: "l"(m), "r"(c0), "r"(c1) : "memory");
}
__device__ __forceinline__ void wg_fence() { asm volatile("wgmma.fence.sync.aligned;" ::: "memory"); }
__device__ __forceinline__ void wg_commit() { asm volatile("wgmma.commit_group.sync.aligned;" ::: "memory"); }
template <int N> __device__ __forceinline__ void wg_wait() { asm volatile("wgmma.wait_group.sync.aligned %0;" :: "n"(N) : "memory"); }
template <int N> __device__ __forceinline__ void reg_fence(float (&d)[N]) {
#pragma unroll
  for (int i = 0; i < N; i++) asm volatile("" : "+f"(d[i]) :: "memory");
}
__device__ __forceinline__ void wgmma4_n128_tb0(float (&d)[64], uint32_t a, uint32_t b, int scale_d) {
  asm volatile("{\n.reg .pred p;\n.reg .b32 la, lb, hi;\n.reg .b64 da, db;\nsetp.ne.b32 p, %66, 0;\nmov.b32 hi, 0x40000040;\n"
    "add.u32 la, %64, 0;\nadd.u32 lb, %65, 0;\nmov.b64 da, {la, hi};\nmov.b64 db, {lb, hi};\n"
    "wgmma.mma_async.sync.aligned.m64n128k16.f32.bf16.bf16 "
    "{%0, %1, %2, %3, %4, %5, %6, %7, %8, %9, %10, %11, %12, %13, %14, %15, %16, %17, %18, %19, %20, %21, %22, %23, %24, %25, %26, %27, %28, %29, %30, %31, %32, %33, %34, %35, %36, %37, %38, %39, %40, %41, %42, %43, %44, %45, %46, %47, %48, %49, %50, %51, %52, %53, %54, %55, %56, %57, %58, %59, %60, %61, %62, %63}, "
    "da, db, p, 1, 1, 0, 0;\n"
    "add.u32 la, %64, 2;\nadd.u32 lb, %65, 2;\nmov.b64 da, {la, hi};\nmov.b64 db, {lb, hi};\n"
    "wgmma.mma_async.sync.aligned.m64n128k16.f32.bf16.bf16 "
    "{%0, %1, %2, %3, %4, %5, %6, %7, %8, %9, %10, %11, %12, %13, %14, %15, %16, %17, %18, %19, %20, %21, %22, %23, %24, %25, %26, %27, %28, %29, %30, %31, %32, %33, %34, %35, %36, %37, %38, %39, %40, %41, %42, %43, %44, %45, %46, %47, %48, %49, %50, %51, %52, %53, %54, %55, %56, %57, %58, %59, %60, %61, %62, %63}, "
    "da, db, 1, 1, 1, 0, 0;\n"
    "add.u32 la, %64, 4;\nadd.u32 lb, %65, 4;\nmov.b64 da, {la, hi};\nmov.b64 db, {lb, hi};\n"
    "wgmma.mma_async.sync.aligned.m64n128k16.f32.bf16.bf16 "
    "{%0, %1, %2, %3, %4, %5, %6, %7, %8, %9, %10, %11, %12, %13, %14, %15, %16, %17, %18, %19, %20, %21, %22, %23, %24, %25, %26, %27, %28, %29, %30, %31, %32, %33, %34, %35, %36, %37, %38, %39, %40, %41, %42, %43, %44, %45, %46, %47, %48, %49, %50, %51, %52, %53, %54, %55, %56, %57, %58, %59, %60, %61, %62, %63}, "
    "da, db, 1, 1, 1, 0, 0;\n"
    "add.u32 la, %64, 6;\nadd.u32 lb, %65, 6;\nmov.b64 da, {la, hi};\nmov.b64 db, {lb, hi};\n"
    "wgmma.mma_async.sync.aligned.m64n128k16.f32.bf16.bf16 "
    "{%0, %1, %2, %3, %4, %5, %6, %7, %8, %9, %10, %11, %12, %13, %14, %15, %16, %17, %18, %19, %20, %21, %22, %23, %24, %25, %26, %27, %28, %29, %30, %31, %32, %33, %34, %35, %36, %37, %38, %39, %40, %41, %42, %43, %44, %45, %46, %47, %48, %49, %50, %51, %52, %53, %54, %55, %56, %57, %58, %59, %60, %61, %62, %63}, "
    "da, db, 1, 1, 1, 0, 0;\n"
    "}\n"
    : "+f"(d[0]), "+f"(d[1]), "+f"(d[2]), "+f"(d[3]), "+f"(d[4]), "+f"(d[5]), "+f"(d[6]), "+f"(d[7]), "+f"(d[8]), "+f"(d[9]), "+f"(d[10]), "+f"(d[11]), "+f"(d[12]), "+f"(d[13]), "+f"(d[14]), "+f"(d[15]), "+f"(d[16]), "+f"(d[17]), "+f"(d[18]), "+f"(d[19]), "+f"(d[20]), "+f"(d[21]), "+f"(d[22]), "+f"(d[23]), "+f"(d[24]), "+f"(d[25]), "+f"(d[26]), "+f"(d[27]), "+f"(d[28]), "+f"(d[29]), "+f"(d[30]), "+f"(d[31]), "+f"(d[32]), "+f"(d[33]), "+f"(d[34]), "+f"(d[35]), "+f"(d[36]), "+f"(d[37]), "+f"(d[38]), "+f"(d[39]), "+f"(d[40]), "+f"(d[41]), "+f"(d[42]), "+f"(d[43]), "+f"(d[44]), "+f"(d[45]), "+f"(d[46]), "+f"(d[47]), "+f"(d[48]), "+f"(d[49]), "+f"(d[50]), "+f"(d[51]), "+f"(d[52]), "+f"(d[53]), "+f"(d[54]), "+f"(d[55]), "+f"(d[56]), "+f"(d[57]), "+f"(d[58]), "+f"(d[59]), "+f"(d[60]), "+f"(d[61]), "+f"(d[62]), "+f"(d[63])
    : "r"(a), "r"(b), "r"(scale_d));
}
__device__ __forceinline__ void wgmma4_n128_tb1(float (&d)[64], uint32_t a, uint32_t b, int scale_d) {
  asm volatile("{\n.reg .pred p;\n.reg .b32 la, lb, hi;\n.reg .b64 da, db;\nsetp.ne.b32 p, %66, 0;\nmov.b32 hi, 0x40000040;\n"
    "add.u32 la, %64, 0;\nadd.u32 lb, %65, 0;\nmov.b64 da, {la, hi};\nmov.b64 db, {lb, hi};\n"
    "wgmma.mma_async.sync.aligned.m64n128k16.f32.bf16.bf16 "
    "{%0, %1, %2, %3, %4, %5, %6, %7, %8, %9, %10, %11, %12, %13, %14, %15, %16, %17, %18, %19, %20, %21, %22, %23, %24, %25, %26, %27, %28, %29, %30, %31, %32, %33, %34, %35, %36, %37, %38, %39, %40, %41, %42, %43, %44, %45, %46, %47, %48, %49, %50, %51, %52, %53, %54, %55, %56, %57, %58, %59, %60, %61, %62, %63}, "
    "da, db, p, 1, 1, 0, 1;\n"
    "add.u32 la, %64, 2;\nadd.u32 lb, %65, 128;\nmov.b64 da, {la, hi};\nmov.b64 db, {lb, hi};\n"
    "wgmma.mma_async.sync.aligned.m64n128k16.f32.bf16.bf16 "
    "{%0, %1, %2, %3, %4, %5, %6, %7, %8, %9, %10, %11, %12, %13, %14, %15, %16, %17, %18, %19, %20, %21, %22, %23, %24, %25, %26, %27, %28, %29, %30, %31, %32, %33, %34, %35, %36, %37, %38, %39, %40, %41, %42, %43, %44, %45, %46, %47, %48, %49, %50, %51, %52, %53, %54, %55, %56, %57, %58, %59, %60, %61, %62, %63}, "
    "da, db, 1, 1, 1, 0, 1;\n"
    "add.u32 la, %64, 4;\nadd.u32 lb, %65, 256;\nmov.b64 da, {la, hi};\nmov.b64 db, {lb, hi};\n"
    "wgmma.mma_async.sync.aligned.m64n128k16.f32.bf16.bf16 "
    "{%0, %1, %2, %3, %4, %5, %6, %7, %8, %9, %10, %11, %12, %13, %14, %15, %16, %17, %18, %19, %20, %21, %22, %23, %24, %25, %26, %27, %28, %29, %30, %31, %32, %33, %34, %35, %36, %37, %38, %39, %40, %41, %42, %43, %44, %45, %46, %47, %48, %49, %50, %51, %52, %53, %54, %55, %56, %57, %58, %59, %60, %61, %62, %63}, "
    "da, db, 1, 1, 1, 0, 1;\n"
    "add.u32 la, %64, 6;\nadd.u32 lb, %65, 384;\nmov.b64 da, {la, hi};\nmov.b64 db, {lb, hi};\n"
    "wgmma.mma_async.sync.aligned.m64n128k16.f32.bf16.bf16 "
    "{%0, %1, %2, %3, %4, %5, %6, %7, %8, %9, %10, %11, %12, %13, %14, %15, %16, %17, %18, %19, %20, %21, %22, %23, %24, %25, %26, %27, %28, %29, %30, %31, %32, %33, %34, %35, %36, %37, %38, %39, %40, %41, %42, %43, %44, %45, %46, %47, %48, %49, %50, %51, %52, %53, %54, %55, %56, %57, %58, %59, %60, %61, %62, %63}, "
    "da, db, 1, 1, 1, 0, 1;\n"
    "}\n"
    : "+f"(d[0]), "+f"(d[1]), "+f"(d[2]), "+f"(d[3]), "+f"(d[4]), "+f"(d[5]), "+f"(d[6]), "+f"(d[7]), "+f"(d[8]), "+f"(d[9]), "+f"(d[10]), "+f"(d[11]), "+f"(d[12]), "+f"(d[13]), "+f"(d[14]), "+f"(d[15]), "+f"(d[16]), "+f"(d[17]), "+f"(d[18]), "+f"(d[19]), "+f"(d[20]), "+f"(d[21]), "+f"(d[22]), "+f"(d[23]), "+f"(d[24]), "+f"(d[25]), "+f"(d[26]), "+f"(d[27]), "+f"(d[28]), "+f"(d[29]), "+f"(d[30]), "+f"(d[31]), "+f"(d[32]), "+f"(d[33]), "+f"(d[34]), "+f"(d[35]), "+f"(d[36]), "+f"(d[37]), "+f"(d[38]), "+f"(d[39]), "+f"(d[40]), "+f"(d[41]), "+f"(d[42]), "+f"(d[43]), "+f"(d[44]), "+f"(d[45]), "+f"(d[46]), "+f"(d[47]), "+f"(d[48]), "+f"(d[49]), "+f"(d[50]), "+f"(d[51]), "+f"(d[52]), "+f"(d[53]), "+f"(d[54]), "+f"(d[55]), "+f"(d[56]), "+f"(d[57]), "+f"(d[58]), "+f"(d[59]), "+f"(d[60]), "+f"(d[61]), "+f"(d[62]), "+f"(d[63])
    : "r"(a), "r"(b), "r"(scale_d));
}
__device__ __forceinline__ void wgmma4_n96_tb1(float (&d)[48], uint32_t a, uint32_t b, int scale_d) {
  asm volatile("{\n.reg .pred p;\n.reg .b32 la, lb, hi;\n.reg .b64 da, db;\nsetp.ne.b32 p, %50, 0;\nmov.b32 hi, 0x40000040;\n"
    "add.u32 la, %48, 0;\nadd.u32 lb, %49, 0;\nmov.b64 da, {la, hi};\nmov.b64 db, {lb, hi};\n"
    "wgmma.mma_async.sync.aligned.m64n96k16.f32.bf16.bf16 "
    "{%0, %1, %2, %3, %4, %5, %6, %7, %8, %9, %10, %11, %12, %13, %14, %15, %16, %17, %18, %19, %20, %21, %22, %23, %24, %25, %26, %27, %28, %29, %30, %31, %32, %33, %34, %35, %36, %37, %38, %39, %40, %41, %42, %43, %44, %45, %46, %47}, "
    "da, db, p, 1, 1, 0, 1;\n"
    "add.u32 la, %48, 2;\nadd.u32 lb, %49, 128;\nmov.b64 da, {la, hi};\nmov.b64 db, {lb, hi};\n"
    "wgmma.mma_async.sync.aligned.m64n96k16.f32.bf16.bf16 "
    "{%0, %1, %2, %3, %4, %5, %6, %7, %8, %9, %10, %11, %12, %13, %14, %15, %16, %17, %18, %19, %20, %21, %22, %23, %24, %25, %26, %27, %28, %29, %30, %31, %32, %33, %34, %35, %36, %37, %38, %39, %40, %41, %42, %43, %44, %45, %46, %47}, "
    "da, db, 1, 1, 1, 0, 1;\n"
    "add.u32 la, %48, 4;\nadd.u32 lb, %49, 256;\nmov.b64 da, {la, hi};\nmov.b64 db, {lb, hi};\n"
    "wgmma.mma_async.sync.aligned.m64n96k16.f32.bf16.bf16 "
    "{%0, %1, %2, %3, %4, %5, %6, %7, %8, %9, %10, %11, %12, %13, %14, %15, %16, %17, %18, %19, %20, %21, %22, %23, %24, %25, %26, %27, %28, %29, %30, %31, %32, %33, %34, %35, %36, %37, %38, %39, %40, %41, %42, %43, %44, %45, %46, %47}, "
    "da, db, 1, 1, 1, 0, 1;\n"
    "add.u32 la, %48, 6;\nadd.u32 lb, %49, 384;\nmov.b64 da, {la, hi};\nmov.b64 db, {lb, hi};\n"
    "wgmma.mma_async.sync.aligned.m64n96k16.f32.bf16.bf16 "
    "{%0, %1, %2, %3, %4, %5, %6, %7, %8, %9, %10, %11, %12, %13, %14, %15, %16, %17, %18, %19, %20, %21, %22, %23, %24, %25, %26, %27, %28, %29, %30, %31, %32, %33, %34, %35, %36, %37, %38, %39, %40, %41, %42, %43, %44, %45, %46, %47}, "
    "da, db, 1, 1, 1, 0, 1;\n"
    "}\n"
    : "+f"(d[0]), "+f"(d[1]), "+f"(d[2]), "+f"(d[3]), "+f"(d[4]), "+f"(d[5]), "+f"(d[6]), "+f"(d[7]), "+f"(d[8]), "+f"(d[9]), "+f"(d[10]), "+f"(d[11]), "+f"(d[12]), "+f"(d[13]), "+f"(d[14]), "+f"(d[15]), "+f"(d[16]), "+f"(d[17]), "+f"(d[18]), "+f"(d[19]), "+f"(d[20]), "+f"(d[21]), "+f"(d[22]), "+f"(d[23]), "+f"(d[24]), "+f"(d[25]), "+f"(d[26]), "+f"(d[27]), "+f"(d[28]), "+f"(d[29]), "+f"(d[30]), "+f"(d[31]), "+f"(d[32]), "+f"(d[33]), "+f"(d[34]), "+f"(d[35]), "+f"(d[36]), "+f"(d[37]), "+f"(d[38]), "+f"(d[39]), "+f"(d[40]), "+f"(d[41]), "+f"(d[42]), "+f"(d[43]), "+f"(d[44]), "+f"(d[45]), "+f"(d[46]), "+f"(d[47])
    : "r"(a), "r"(b), "r"(scale_d));
}

__device__ __forceinline__ void bar_arrive(int id, int n) { asm volatile("bar.arrive %0, %1;" :: "r"(id), "r"(n) : "memory"); }
__device__ __forceinline__ void bar_sync(int id, int n) { asm volatile("bar.sync %0, %1;" :: "r"(id), "r"(n) : "memory"); }
__device__ __forceinline__ unsigned ld_rlx(const unsigned* p) { unsigned v; asm volatile("ld.relaxed.gpu.global.u32 %0, [%1];" : "=r"(v) : "l"(p) : "memory"); return v; }
__device__ __forceinline__ void red_add(unsigned* p) { asm volatile("red.relaxed.gpu.global.add.u32 [%0], 1;" :: "l"(p) : "memory"); }
__device__ __forceinline__ void wait_cnt(const unsigned* p, unsigned target) {
  for (uint32_t n = 0; n < (1u << 14); n++) if ((int)(ld_rlx(p) - target) >= 0) break;
}
__device__ __forceinline__ float bf_lo(uint32_t v) { return __uint_as_float(v << 16); }
__device__ __forceinline__ float bf_hi(uint32_t v) { return __uint_as_float(v & 0xffff0000u); }
__device__ __forceinline__ uint32_t pack2(float lo, float hi) { uint32_t r; asm("cvt.rn.bf16x2.f32 %0, %1, %2;" : "=r"(r) : "f"(hi), "f"(lo)); return r; }
__device__ __forceinline__ uint32_t pack2v(float lo, float hi) { uint32_t r; asm volatile("cvt.rn.bf16x2.f32 %0, %1, %2;" : "=r"(r) : "f"(hi), "f"(lo)); return r; }
__device__ __forceinline__ float bfr(float v) { return bf_hi(pack2(0.f, v)); }
__device__ __forceinline__ uint32_t tagf(float v, uint32_t tag) { return (__float_as_uint(v) & ~3u) | tag; }
template <int OFF> __device__ __forceinline__ uint4 ld_msg(const void* p) { uint4 v; asm volatile("ld.relaxed.gpu.global.v4.u32 {%0,%1,%2,%3}, [%4 + %5];" : "=r"(v.x), "=r"(v.y), "=r"(v.z), "=r"(v.w) : "l"(p), "n"(OFF) : "memory"); return v; }
__device__ __forceinline__ void st_msg(void* p, uint32_t a, uint32_t b, uint32_t c, uint32_t d) { asm volatile("st.relaxed.gpu.global.v4.u32 [%0], {%1,%2,%3,%4};" :: "l"(p), "r"(a), "r"(b), "r"(c), "r"(d) : "memory"); }
__device__ __forceinline__ uint32_t stale(const uint4& v, uint32_t tag) { return ((v.x ^ tag) | (v.y ^ tag) | (v.z ^ tag) | (v.w ^ tag)) & 3u; }
__device__ __forceinline__ void sts4(uint32_t a, uint32_t x, uint32_t y, uint32_t z, uint32_t w) { asm volatile("st.shared.v4.u32 [%0], {%1,%2,%3,%4};" :: "r"(a), "r"(x), "r"(y), "r"(z), "r"(w) : "memory"); }
__device__ __forceinline__ void tma_st2d(const CUtensorMap* m, uint32_t src, int c0, int c1) {
  asm volatile("cp.async.bulk.tensor.2d.global.shared::cta.bulk_group [%0, {%2, %3}], [%1];" :: "l"(m), "r"(src), "r"(c0), "r"(c1) : "memory");
}
__device__ __forceinline__ void tma_st3d(const CUtensorMap* m, uint32_t src, int c0, int c1, int c2) {
  asm volatile("cp.async.bulk.tensor.3d.global.shared::cta.bulk_group [%0, {%2, %3, %4}], [%1];" :: "l"(m), "r"(src), "r"(c0), "r"(c1), "r"(c2) : "memory");
}
__device__ __forceinline__ float rcp_f(float v) { float r; asm("rcp.approx.f32 %0, %1;" : "=f"(r) : "f"(v)); return r; }
__device__ __forceinline__ float sqrt_f(float v) { float r; asm("sqrt.approx.f32 %0, %1;" : "=f"(r) : "f"(v)); return r; }
__device__ __forceinline__ float tanh_f(float v) { float r; asm("tanh.approx.f32 %0, %1;" : "=f"(r) : "f"(v)); return r; }
__device__ __forceinline__ float gelu_half(float hf) {
  const float k0 = 2.0f * 0.7978845608028654f, k1 = 8.0f * 0.7978845608028654f * 0.044715f;
  return fmaf(hf, tanh_f(hf * fmaf(hf * hf, k1, k0)), hf);
}
__device__ __forceinline__ uint2 ld_msg2(const void* p) { uint2 v; asm volatile("ld.relaxed.gpu.global.v2.u32 {%0,%1}, [%2];" : "=r"(v.x), "=r"(v.y) : "l"(p) : "memory"); return v; }
__device__ __forceinline__ void fence_async_smem() { asm volatile("fence.proxy.async.shared::cta;" ::: "memory"); }
template <int OFF> __device__ __forceinline__ uint4 ldg_nc(const void* p) { uint4 v; asm volatile("ld.global.nc.v4.u32 {%0,%1,%2,%3}, [%4 + %5];" : "=r"(v.x), "=r"(v.y), "=r"(v.z), "=r"(v.w) : "l"(p), "n"(OFF)); return v; }
template <int OFF> __device__ __forceinline__ uint4 ldg_ord(const void* p) { uint4 v; asm volatile("ld.global.L1::no_allocate.v4.u32 {%0,%1,%2,%3}, [%4 + %5];" : "=r"(v.x), "=r"(v.y), "=r"(v.z), "=r"(v.w) : "l"(p), "n"(OFF) : "memory"); return v; }
__device__ __forceinline__ void stg4(void* p, uint32_t a, uint32_t b, uint32_t c, uint32_t d) { asm volatile("st.global.v4.u32 [%0], {%1,%2,%3,%4};" :: "l"(p), "r"(a), "r"(b), "r"(c), "r"(d) : "memory"); }
__device__ __forceinline__ float4 lds4f(uint32_t a) { float4 v; asm volatile("ld.shared.v4.f32 {%0,%1,%2,%3}, [%4];" : "=f"(v.x), "=f"(v.y), "=f"(v.z), "=f"(v.w) : "r"(a)); return v; }
__device__ __forceinline__ uint4 lds4u(uint32_t a) { uint4 v; asm volatile("ld.shared.v4.u32 {%0,%1,%2,%3}, [%4];" : "=r"(v.x), "=r"(v.y), "=r"(v.z), "=r"(v.w) : "r"(a) : "memory"); return v; }
__device__ __forceinline__ float2 lds2f(uint32_t a) { float2 v; asm volatile("ld.shared.v2.f32 {%0,%1}, [%2];" : "=f"(v.x), "=f"(v.y) : "r"(a)); return v; }
__device__ __forceinline__ void st_async4(uint32_t raddr, uint32_t a, uint32_t b, uint32_t c, uint32_t d, uint32_t rbar) {
  asm volatile("st.async.weak.shared::cluster.mbarrier::complete_tx::bytes.v4.b32 [%0], {%1,%2,%3,%4}, [%5];"
    :: "r"(raddr), "r"(a), "r"(b), "r"(c), "r"(d), "r"(rbar) : "memory");
}

struct Ctx {
  uint32_t sm;
  uint32_t da;
  uint32_t db;
  bool lead;
  int trs;
};
template <int V> struct IC { static constexpr int value = V; };
template <int S0, int S1, class F>
__device__ __forceinline__ void static_for(F&& f) {
  if constexpr (S0 < S1) { f(IC<S0>{}); static_for<S0 + 1, S1>(f); }
}
template <int N, int TB>
__device__ __forceinline__ void mma_issue(float (&acc)[N / 2], const Ctx& c, uint32_t offa, uint32_t offb, int accum) {
  const uint32_t a = c.da + (offa >> 4), b = c.db + (offb >> 4) + (TB ? (512u << 16) : (1u << 16));
  wg_fence();
  if constexpr (N == 128 && TB == 0) wgmma4_n128_tb0(acc, a, b, accum);
  if constexpr (N == 128 && TB == 1) wgmma4_n128_tb1(acc, a, b, accum);
  if constexpr (N == 96) wgmma4_n96_tb1(acc, a, b, accum);
  wg_commit();
}
template <int N, int S>
__device__ __forceinline__ void step1(float (&acc)[N / 2], const Ctx& c) {
  if (S < 8) mbar_wait(c.sm + OFF_BAR + BAR_XF + 8 * S, 0);
  mbar_wait(c.sm + OFF_BAR + BAR_BF + 8 * (S % NB1), (S / NB1) & 1);
  if (threadIdx.x == 0) TR(S, 3);
  mma_issue<N, 1>(acc, c, xslot(S & 7), bslot(S % NB1), (S & 7) != 0);
}
template <int TB>
__device__ __forceinline__ void step2(float (&acc)[64], Ctx& c, int st, uint32_t ph, int accum) {
  mbar_wait(c.sm + OFF_BAR + BAR_FULL + 8 * st, ph);
  mma_issue<128, TB>(acc, c, st * STB, st * STB + 16384, accum);
}
__device__ __forceinline__ void release2(const Ctx& c, int st) {
  if (c.lead) mbar_arrive(c.sm + OFF_BAR + BAR_EMPTY + 8 * st);
}
template <int S>
__device__ __forceinline__ void release(const Ctx& c) {
  if constexpr (S < S_S) {
    if (c.lead) {
      if constexpr (S + NB1 < S_S) mbar_arrive(c.sm + OFF_BAR + BAR_BE + 8 * (S % NB1));
      if constexpr (S == 9) mbar_arrive(c.sm + OFF_BAR + BAR_EMPTY);
      if constexpr (S >= 11) mbar_arrive(c.sm + OFF_BAR + BAR_EMPTY + 8 * (S - 10));
    }
  } else if constexpr (S < S_END - NST) {
    release2(c, stage_of(S));
  }
}

struct HEpi { float a0, b0, a1, b1; uint32_t vec, stg, never; uint32_t w0[4], w1[4]; };
template <int G, int I, bool WAIT, int NA>
__device__ __forceinline__ void h_unit(const float (&acc)[NA], HEpi& e, const float4 v, uint32_t free_bar, uint32_t free_par, int bar_id) {
  const int r = 4 * (4 * G + I);
  e.w0[I] = pack2v(gelu_half(fmaf(e.a0, acc[r], fmaf(e.b0, v.x, v.z))), gelu_half(fmaf(e.a0, acc[r + 1], fmaf(e.b0, v.y, v.w))));
  e.w1[I] = pack2v(gelu_half(fmaf(e.a1, acc[r + 2], fmaf(e.b1, v.x, v.z))), gelu_half(fmaf(e.a1, acc[r + 3], fmaf(e.b1, v.y, v.w))));
  if (I < 3)
    asm volatile("{\n.reg .pred p;\nsetp.ne.u32 p, %0, 0;\n@p st.shared.v2.u32 [%1], {%2, %3};\n}" :: "r"(e.never), "r"(e.stg), "r"(e.w0[I]), "r"(e.w1[I]) : "memory");
  if (I == 3) {
    if (WAIT) mbar_wait(free_bar, free_par);
    sts4(e.stg + G * 8192, e.w0[0], e.w0[1], e.w0[2], e.w0[3]);
    sts4(e.stg + G * 8192 + 512, e.w1[0], e.w1[1], e.w1[2], e.w1[3]);
    fence_async_smem();
    bar_arrive(bar_id, 288);
  }
}

__global__ void __cluster_dims__(2, 1, 1) __launch_bounds__(384, 1) fused_kernel(const __grid_constant__ Params p) {
  extern __shared__ __align__(1024) uint8_t smem_raw[];
  const uint32_t sm = (uint32_t)__cvta_generic_to_shared(smem_raw);
  const int tid = threadIdx.x, lane = tid & 31;
  const int warp = __shfl_sync(0xffffffffu, tid >> 5, 0);
  int lc;
  {
    const int c = blockIdx.x >> 1;
    if (c < 4) lc = 4 + c;
    else if (c < 36) lc = ((c - 4) & 7) * 8 + ((c - 4) >> 3);
    else lc = (1 + (c - 36) % 7) * 8 + 4 + (c - 36) / 7;
  }
  int gpc;
  { unsigned smid; asm("mov.u32 %0, %%smid;" : "=r"(smid)); const int t = smid >> 1; gpc = t < 32 ? t & 7 : t < 60 ? 1 + (t - 32) % 7 : t < 62 ? t - 54 : 0; }
  const int rk = blockIdx.x & 1, cb = lc & 3, rb = lc >> 2, j = cb * 2 + rk;
  const int row0 = rb * 128;
  const uint32_t bars = sm + OFF_BAR;
  TLC(0);
#define EPOCH() mbar_wait(bars + BAR_E, 0); unsigned epoch; asm volatile("ld.shared.u32 %0, [%1];" : "=r"(epoch) : "r"(bars + OFF_EPOCH) : "memory"); const uint32_t tag = epoch & 3
  if (warp >= 8) {
    asm volatile("setmaxnreg.dec.sync.aligned.u32 88;");
    if (warp == 8) {
      if (elect_one()) {
        for (int s = 0; s < 8; s++) mbar_init(bars + BAR_XF + 8 * s, 1);
        for (int s = 0; s < NB1; s++) { mbar_init(bars + BAR_BF + 8 * s, 1); mbar_init(bars + BAR_BE + 8 * s, 8); }
        mbar_init(bars + BAR_X16, 1);
        fence_async_smem();
        for (int k = 0; k < 8; k++) {
          mbar_expect_tx(bars + BAR_XF + 8 * k, 16384);
          tma2d(sm + xslot(k), &p.mx, k * 64, row0, bars + BAR_XF + 8 * k);
          if (k < NB1) {
            mbar_expect_tx(bars + BAR_BF + 8 * k, 16384);
            tma3d(sm + bslot(k), &p.mw1, j * 224 + 96, k * 64, 0, bars + BAR_BF + 8 * k);
          }
          if (k == X16_AT) {
            mbar_expect_tx(bars + BAR_X16, 16384);
            tma2d(sm + OFF_STG, &p.mx16, 0, (row0 + j * 16) * 8, bars + BAR_X16);
          }
        }
        for (int s = 0; s < NST; s++) { mbar_init(bars + BAR_FULL + 8 * s, 1); mbar_init(bars + BAR_EMPTY + 8 * s, 8); }
        mbar_init(bars + BAR_V, 2); for (int s = 0; s < 4; s++) mbar_init(bars + BAR_FREE + 8 * s, 1);
        mbar_init(bars + BAR_E, 1); mbar_init(bars + BAR_DEP, 1);
        mbar_init(bars + BAR_M, 1); mbar_init(bars + BAR_Y, 1); mbar_init(bars + BAR_OK, 8);
        asm volatile("fence.mbarrier_init.release.cluster;" ::: "memory");
        fence_async_smem();
        asm volatile("st.shared.u64 [%0], %1;\nst.shared.u32 [%2], %3;" :: "r"(bars + OFF_Z), "l"(0ull), "r"(bars + OFF_STOP), "r"(0) : "memory");
        mbar_expect_tx(bars + BAR_M, 16384);
        mbar_expect_tx(bars + BAR_Y, 16384);
      }
      __syncwarp();
      __syncthreads();
      asm volatile("barrier.cluster.arrive.relaxed.aligned;" ::: "memory");
      if (elect_one()) {
        const CUtensorMap* mc = rk ? &p.mci : &p.mcr;
        const CUtensorMap* md = rk ? &p.mdim : &p.mdre;
        asm volatile("prefetch.tensormap [%0];" :: "l"(mc) : "memory");
        asm volatile("prefetch.tensormap [%0];" :: "l"(&p.mxn) : "memory");
        asm volatile("prefetch.tensormap [%0];" :: "l"(&p.mh) : "memory");
        asm volatile("prefetch.tensormap [%0];" :: "l"(&p.mw2) : "memory");
        asm volatile("prefetch.tensormap [%0];" :: "l"(&p.muv) : "memory");
        asm volatile("prefetch.tensormap [%0];" :: "l"(md) : "memory");
        unsigned long long* pace = &g_pace[gpc * 16];
        unsigned long long nom = 0;
#define PACE(dt)
        for (int k = NB1, i = 0, par = 0; k < S_S; k++) {
          const uint32_t fb = bars + BAR_BF + 8 * i;
          mbar_wait(bars + BAR_BE + 8 * i, par);
          TR(k, 0); PACE(k - NB1 < 8 ? 512 : 384); TR(k, 1);
          mbar_expect_tx(fb, 16384);
          tma3d(sm + bslot(i), &p.mw1, j * 224 + (k < 8 ? 96 : 0), (k & 7) * 64, 0, fb);
          if (k == 10) tma_pf2d(mc, cb * 64, row0);
          if (++i == NB1) { i = 0; par ^= 1; }
        }
        int st = 0; uint32_t ph = 0;
        int trs = S_S;
#define P_ACQ(dt) mbar_wait(bars + BAR_EMPTY + 8 * st, ph); TR(trs, 0); PACE(dt); TR(trs, 1); trs++; const uint32_t fb = bars + BAR_FULL + 8 * st, sa = sm + st * STB, sb = sa + 16384; mbar_expect_tx(fb, DBG_A * 16384 + DBG_B * 16384)
#define P_ADV() if (++st == NST) { st = 0; ph ^= 1; }
        TLREC(11);
        mbar_wait(bars + BAR_DEP, 0);
        asm volatile("fence.proxy.async.global;" ::: "memory");
        TLREC(12);
        for (int k = 0; k < 32; k++) {
          P_ACQ(k < 2 ? 0 : k < 6 ? 384 : 512); if (DBG_A) tma2d(sa, mc, k * 64, row0, fb); if (DBG_B) tma3d(sb, &p.mxn, 0, k * 64, cb * 2, fb); P_ADV();
        }
        TLREC(13);
        mbar_wait(bars + BAR_DEP, 1);
        asm volatile("fence.proxy.async.global;" ::: "memory");
        TLREC(14);
        const int n0 = cb * 128 + rk * 64, n1 = cb * 128 + (rk ^ 1) * 64;
        for (int k = rk * 14; k < rk * 14 + 14; k++) {
          P_ACQ(512); if (DBG_A) tma2d(sa, &p.mh, k * 64, row0, fb); if (DBG_B) { tma5d(sb, &p.mw2, n0, 2 * k, fb); tma5d(sb + 8192, &p.mw2, n1, 2 * k, fb); } P_ADV();
        }
        TLREC(22);
        mbar_wait(bars + BAR_DEP, 0);
        asm volatile("fence.proxy.async.global;" ::: "memory");
        TLREC(23);
        red_add(&g_cnt[C_DONE]);
#pragma unroll 1
        for (int k = 0; k < 8; k++) {
          P_ACQ(512); if (DBG_A) tma2d(sa, &p.muv, k * 64, rk * SEQ + row0, fb); if (DBG_B) { tma5d(sb, md, k * 64, n0 >> 5, fb); tma5d(sb + 8192, md, k * 64, n1 >> 5, fb); } P_ADV();
        }
        asm volatile("st.volatile.shared.u32 [%0], %1;" :: "r"(bars + OFF_STOP), "r"(1) : "memory");
      }
    } else if (warp == 9) {
      unsigned done0 = 0;
      if (lane == 0) done0 = ld_rlx(&g_cnt[C_DONE]);
      __syncthreads();
      asm volatile("barrier.cluster.arrive.relaxed.aligned;" ::: "memory");
      const unsigned epoch = __shfl_sync(0xffffffffu, (done0 >> 7) + 1, 0);
      if (lane == 0) {
        asm volatile("st.shared.u32 [%0], %1;" :: "r"(bars + OFF_EPOCH), "r"(epoch) : "memory");
        mbar_arrive(bars + BAR_E);
        asm volatile("prefetch.tensormap [%0];" :: "l"(&p.sxn) : "memory");
        asm volatile("prefetch.tensormap [%0];" :: "l"(&p.sh) : "memory");
        asm volatile("prefetch.tensormap [%0];" :: "l"(&p.suv) : "memory");
      }
#pragma unroll 1
      for (int ev = 0; ev < 12; ev++) {
        bar_sync(1 + (ev & 3), 288);
        if (lane == 0) {
          const int g = ev < 5 ? ev - 1 : ev < 8 ? ev - 5 : ev - 8;
          if (ev == 0) tma_st2d(&p.sxn, sm + OFF_STG, 0, (row0 + j * 16) * 8);
          else if (ev < 8) tma_st2d(&p.sh, sm + OFF_STG + g * 8192, j * 224 + (ev < 5 ? 96 : 0) + g * 32, row0);
          else tma_st2d(&p.suv, sm + OFF_STG + g * 8192, cb * 128 + g * 32, rk * SEQ + row0);
          asm volatile("cp.async.bulk.commit_group;\ncp.async.bulk.wait_group.read 0;" ::: "memory");
          if (ev == 0) { mbar_arrive(bars + BAR_FREE); mbar_arrive(bars + BAR_FREE + 8); }
          else mbar_arrive(bars + BAR_FREE + 8 * g);
          if (ev == 0 || ev == 7 || ev == 11) {
            unsigned* cnt = &g_cnt[ev == 0 ? C_XN : (ev == 11 ? C_UV : C_H) + rb * 32];
            TLREC(24 + (ev >> 2));
            asm volatile("cp.async.bulk.wait_group 0;" ::: "memory");
            red_add(cnt);
            TLREC(16 + (ev >> 2));
            wait_cnt(cnt, (ev == 0 ? 128 : 8) * epoch);
            mbar_arrive(bars + BAR_DEP);
          }
        }
        __syncwarp();
      }
    } else {
      const int cl = lane < 28 ? lane : 27;
      const __nv_bfloat16* w = p.w1 + (size_t)(rb * 32 + (warp - 10) * 16) * FF + j * 224 + cl * 8;
      __syncthreads();
      asm volatile("barrier.cluster.arrive.relaxed.aligned;" ::: "memory");
      {
        const char* pw = reinterpret_cast<const char*>(p.w1 + (size_t)(rb * 32 + (warp - 10) * 16 + (lane >> 2)) * FF + j * 224) + ((lane & 3) == 3 ? 440 : (lane & 3) * 128);
        asm volatile("prefetch.global.L2 [%0];" :: "l"(pw)); asm volatile("prefetch.global.L2 [%0];" :: "l"(pw + 8 * FF * 2));
      }
      mbar_wait(bars + BAR_XF + 8 * W_DLY, 0);
      {
        uint4 v[16];
        static_for<0, 16>([&](auto I) { v[decltype(I)::value] = ldg_ord<decltype(I)::value * FF * 2>(w); });
        float s[8] = {0.f, 0.f, 0.f, 0.f, 0.f, 0.f, 0.f, 0.f};
#pragma unroll
        for (int r = 0; r < 16; r++) {
          s[0] += bf_lo(v[r].x); s[1] += bf_hi(v[r].x); s[2] += bf_lo(v[r].y); s[3] += bf_hi(v[r].y);
          s[4] += bf_lo(v[r].z); s[5] += bf_hi(v[r].z); s[6] += bf_lo(v[r].w); s[7] += bf_hi(v[r].w);
        }
        float4* s4 = reinterpret_cast<float4*>(smem_raw + OFF_VH);
        if (warp == 11 && lane < 28) { s4[lane * 2] = make_float4(s[0], s[1], s[2], s[3]); s4[lane * 2 + 1] = make_float4(s[4], s[5], s[6], s[7]); }
        bar_sync(5, 64);
        EPOCH();
        if (warp == 10 && lane < 28) {
          const float4 o0 = s4[lane * 2], o1 = s4[lane * 2 + 1];
          float* dst = &g_csw[rb * FF + j * 224 + lane * 8];
          st_msg(dst, tagf(s[0] + o0.x, tag), tagf(s[1] + o0.y, tag), tagf(s[2] + o0.z, tag), tagf(s[3] + o0.w, tag));
          st_msg(dst + 4, tagf(s[4] + o1.x, tag), tagf(s[5] + o1.y, tag), tagf(s[6] + o1.z, tag), tagf(s[7] + o1.w, tag));
          if (lane == 0) TLREC(15);
        }
        bar_sync(5, 64);
      }
      EPOCH();
      const int q = (warp - 10) * 28 + cl;
      const uint2 bb = *reinterpret_cast<const uint2*>(p.b1 + j * 224 + q * 4);
      if (warp == 11) {
        const uint32_t b2v = *reinterpret_cast<const uint32_t*>(p.b2 + cb * 128 + rk * 64 + lane * 2);
        *reinterpret_cast<float2*>(smem_raw + OFF_B2 + lane * 8) = make_float2(0.5f * bf_lo(b2v), 0.5f * bf_hi(b2v));
      }
      float4 acc;
      mbar_wait(bars + BAR_BF + 8 * (G_DLY % NB1), (G_DLY / NB1) & 1);
      for (uint32_t n = 0; n < (1u << 14); n++) {
        uint32_t bad = 0;
        acc = make_float4(0.f, 0.f, 0.f, 0.f);
        uint4 m[16];
        static_for<0, 16>([&](auto I) { m[decltype(I)::value] = ld_msg<decltype(I)::value * FF * 4>(&g_csw[j * 224 + q * 4]); });
#pragma unroll
        for (int r = 0; r < 16; r++) {
          bad |= m[r].x ^ tag;
          acc.x += __uint_as_float(m[r].x); acc.y += __uint_as_float(m[r].y); acc.z += __uint_as_float(m[r].z); acc.w += __uint_as_float(m[r].w);
        }
        if (!__any_sync(0xffffffffu, bad & 3u)) break;
        __nanosleep(300);
      }
      if (lane < 28) {
        float4* s4 = reinterpret_cast<float4*>(smem_raw + OFF_VH);
        s4[q * 2] = make_float4(acc.x, acc.y, 0.5f * bf_lo(bb.x), 0.5f * bf_hi(bb.x));
        s4[q * 2 + 1] = make_float4(acc.z, acc.w, 0.5f * bf_lo(bb.y), 0.5f * bf_hi(bb.y));
      }
      __syncwarp();
      if (lane == 0) { mbar_arrive(bars + BAR_V); if (warp == 10) TLREC(20); }
    }
  } else {
    asm volatile("setmaxnreg.inc.sync.aligned.u32 208;");
    __syncthreads();
    asm volatile("barrier.cluster.arrive.relaxed.aligned;" ::: "memory");
    Ctx c; c.sm = sm; c.lead = lane == 0; c.trs = S_S;
    c.da = (((sm + (warp >> 2) * 8192) & 0x3FFFF) >> 4) | (1u << 16); c.db = (sm & 0x3FFFF) >> 4;
    const int rl = warp * 16 + (lane >> 2);
    float Q[64], R[48], U[64], M[64], Y[64];
    HEpi e;
    e.vec = sm + OFF_VH + (lane & 3) * 16; e.stg = sm + OFF_STG + rl * 64 + (lane & 3) * 16;
    e.never = gridDim.y - 1;
    uint2 m0, m1;
    uint32_t xw[4][4];
    float mu[2], qq[2];
    uint32_t pv[2];
    static_for<0, S_ROLL>([&](auto S_) {
      constexpr int S = decltype(S_)::value;
      float4 hv[2];
      if constexpr (S > HS0) static_for<units_done(S - 1), units_done(S)>([&](auto U_) { hv[decltype(U_)::value - units_done(S - 1)] = lds4f(e.vec + hvec(decltype(U_)::value)); });
      if constexpr (S < 8) step1<128, S>(Q, c);
      else if constexpr (S < S_S) step1<96, S>(R, c);
      else step2<1>(U, c, stage_of(S), par_of(S), S > S_S);
      if (S == 0) TLC(1);
      if (S == HS0 - SLD) { m0 = ld_msg2(&g_stats[row0 + rl]); m1 = ld_msg2(&g_stats[row0 + rl + 8]); }
      if constexpr (S > 0) { wg_wait<1>(); release<S - 1>(c); }
      if (S == XS0) {
        mbar_wait(bars + BAR_X16, 0);
#pragma unroll
        for (int t = 0; t < 4; t++) {
          const int kc = (t & 1) * 4 + (lane >> 3);
          const uint4 v = lds4u(sm + OFF_STG + (warp * 2 + (t >> 1)) * 1024 + kc * 128 + (((lane & 7) ^ kc) << 4));
          xw[t][0] = v.x; xw[t][1] = v.y; xw[t][2] = v.z; xw[t][3] = v.w;
        }
        pv[0] = __byte_perm(__shfl_sync(0xffffffffu, xw[0][0], 0), 0, 0x1010); pv[1] = __byte_perm(__shfl_sync(0xffffffffu, xw[2][0], 0), 0, 0x1010);
      }
      if constexpr (S == XS0 + 1 || S == XS0 + 2) {
        constexpr int r = S - XS0 - 1;
        float a = 0.f, b = 0.f, qa = 0.f, qb = 0.f;
#pragma unroll
        for (int i = 0; i < 8; i++) {
          uint32_t d;
          asm("sub.rn.bf16x2 %0, %1, %2;" : "=r"(d) : "r"(xw[2 * r + (i >> 2)][i & 3]), "r"(pv[r]));
          a += bf_lo(d); b += bf_hi(d); qa = fmaf(bf_lo(d), bf_lo(d), qa); qb = fmaf(bf_hi(d), bf_hi(d), qb);
        }
        const float s1 = a + b, s2 = qa + qb;
        mu[r] = ((lane & 1) ? s2 : s1) + __shfl_xor_sync(0xffffffffu, (lane & 1) ? s1 : s2, 1);
      }
      if (S == XS0 + 3) {
        float t = ((lane & 2) ? mu[1] : mu[0]) + __shfl_xor_sync(0xffffffffu, (lane & 2) ? mu[0] : mu[1], 2);
#pragma unroll
        for (int o = 4; o < 32; o <<= 1) t += __shfl_xor_sync(0xffffffffu, t, o);
        const float o1 = __shfl_xor_sync(0xffffffffu, t, 1);
        const float s1 = ((lane & 1) ? o1 : t) * (1.0f / DM), s2 = (lane & 1) ? t : o1;
        mu[0] = bf_lo((lane & 2) ? pv[1] : pv[0]) + s1;
        mu[1] = fmaxf(fmaf(s2, 1.0f / DM, -s1 * s1), 0.f);
      }
      if (S == XS0 + 4) {
        const float mean = mu[0], var = mu[1], m1 = bfr(mean);
        const float i1 = rcp_f(bfr(sqrt_f(bfr(bfr(var) + 1e-5f))));
        const float i2 = 0.5f * rcp_f(bfr(sqrt_f(bfr(bfr(var * i1 * i1) + 1e-5f))));
        const float rh = bfr(i1);
        const uint32_t hl = pack2(rh, i1 - rh), mm = pack2(m1, m1);
        mu[0] = i1 * i2; mu[1] = -(m1 * i1 + bfr((mean - m1) * i1)) * i2;
        qq[0] = __uint_as_float(__shfl_sync(0xffffffffu, hl, 0)); qq[1] = __uint_as_float(__shfl_sync(0xffffffffu, hl, 2));
        pv[0] = __shfl_sync(0xffffffffu, mm, 0); pv[1] = __shfl_sync(0xffffffffu, mm, 2);
      }
      if (S == XS0 + 5) {
#pragma unroll
        for (int r = 0; r < 2; r++) {
          const uint32_t t = __float_as_uint(qq[r]), hi = __byte_perm(t, 0, 0x1010), lo = __byte_perm(t, 0, 0x3232);
#pragma unroll
          for (int i = 0; i < 8; i++) {
            uint32_t& w = xw[2 * r + (i >> 2)][i & 3];
            asm("{\n.reg .b32 t;\nsub.rn.bf16x2 %0, %0, %3;\nmul.rn.bf16x2 t, %0, %2;\nfma.rn.bf16x2 %0, %0, %1, t;\n}" : "+r"(w) : "r"(hi), "r"(lo), "r"(pv[r]));
          }
        }
#pragma unroll
        for (int t = 0; t < 4; t++) {
          const int kc = (t & 1) * 4 + ((lane & 7) >> 1);
          asm volatile("stmatrix.sync.aligned.m8n8.x4.shared.b16 [%0], {%1,%2,%3,%4};"
                       :: "r"(sm + OFF_STG + (warp * 2 + (t >> 1)) * 1024 + kc * 128 + ((((lane & 1) * 4 + (lane >> 3)) ^ kc) << 4)),
                          "r"(xw[t][0]), "r"(xw[t][1]), "r"(xw[t][2]), "r"(xw[t][3]) : "memory");
        }
        fence_async_smem();
        bar_arrive(1, 288);
        TLC(28);
      }
      if (S == XS0 + 6) {
        EPOCH();
        if ((lane & ~2) == 0)
          asm volatile("st.relaxed.gpu.global.v2.u32 [%0], {%1,%2};" :: "l"(&g_stats[row0 + j * 16 + warp * 2 + (lane >> 1)]), "r"(tagf(mu[0], tag)), "r"(tagf(mu[1], tag)) : "memory");
      }
      if (S == 8) { reg_fence(Q); TLC(2); }
      if (S == S_S) { reg_fence(R); TLC(3); }
      if (S == HS0) {
        EPOCH();
        for (uint32_t n = 0; n < (1u << 14) && (((m0.x ^ tag) | (m0.y ^ tag) | (m1.x ^ tag) | (m1.y ^ tag)) & 3u); n++) {
          __nanosleep(200);
          m0 = ld_msg2(&g_stats[row0 + rl]); m1 = ld_msg2(&g_stats[row0 + rl + 8]);
        }
        e.a0 = __uint_as_float(m0.x); e.b0 = __uint_as_float(m0.y); e.a1 = __uint_as_float(m1.x); e.b1 = __uint_as_float(m1.y);
        mbar_wait(bars + BAR_V, 0);
        TLC(21);
      }
      static_for<units_done(S - 1), units_done(S)>([&](auto U_) {
        constexpr int u = decltype(U_)::value, G = u < 16 ? u / 4 : (u - 16) / 4, ev = 1 + u / 4;
        if (S == HS0) hv[0] = lds4f(e.vec + hvec(u));
        const float4 v = hv[u - units_done(S - 1)];
        if constexpr (u < 16) h_unit<G, u % 4, (G < 2)>(Q, e, v, bars + BAR_FREE + 8 * G, 0, 1 + (ev & 3));
        else h_unit<G, u % 4, true>(R, e, v, bars + BAR_FREE + 8 * G, G < 2, 1 + (ev & 3));
      });
    });
    TLC(4);
    int st = stage_of(S_ROLL), pst = stage_of(S_ROLL - 1); uint32_t ph = par_of(S_ROLL);
#pragma unroll 1
    for (int s = S_ROLL; s < S_M; s++) {
      step2<1>(U, c, st, ph, 1);
      wg_wait<1>();
      release2(c, pst);
      pst = st; if (++st == NST) { st = 0; ph ^= 1; }
    }
    TLC(5);
    static_for<S_M, S_M + UVN>([&](auto S_) {
      constexpr int S = decltype(S_)::value;
      step2<1>(M, c, stage_of(S), par_of(S), S > S_M);
      wg_wait<1>();
      release<S - 1>(c);
      if (S == S_M) reg_fence(U);
      static_for<(S - S_M) * 4 / UVN, (S - S_M + 1) * 4 / UVN>([&](auto G_) {
        constexpr int G = decltype(G_)::value, r = 16 * G;
        mbar_wait(bars + BAR_FREE + 8 * G, G < 2 ? 0 : G == 2 ? 1 : 0);
        sts4(e.stg + G * 8192, pack2(U[r], U[r + 1]), pack2(U[r + 4], U[r + 5]), pack2(U[r + 8], U[r + 9]), pack2(U[r + 12], U[r + 13]));
        sts4(e.stg + G * 8192 + 512, pack2(U[r + 2], U[r + 3]), pack2(U[r + 6], U[r + 7]), pack2(U[r + 10], U[r + 11]), pack2(U[r + 14], U[r + 15]));
        fence_async_smem();
        bar_arrive(1 + G, 288);
      });
    });
    st = stage_of(S_M + UVN); pst = stage_of(S_M + UVN - 1); ph = par_of(S_M + UVN);
#pragma unroll 1
    for (int s = S_M + UVN; s < S_Y; s++) {
      step2<1>(M, c, st, ph, 1);
      wg_wait<1>();
      release2(c, pst);
      pst = st; if (++st == NST) { st = 0; ph ^= 1; }
    }
    TLC(6);
    const size_t ooff = (size_t)(row0 + rl) * DM + cb * 128 + rk * 64 + (lane & 3) * 8;
    const uint32_t mine = warp * 4096 + lane * 16, peer = rk ^ 1, sgn = rk ? 0x80008000u : 0u;
    uint4 g[4], xr[4];
    static_for<S_Y, S_END>([&](auto S_) {
      constexpr int S = decltype(S_)::value;
      step2<0>(Y, c, stage_of(S), par_of(S), S > S_Y);
      wg_wait<1>();
      release<S - 1>(c);
      if (S == S_Y) {
        reg_fence(M);
        asm volatile("barrier.cluster.wait.aligned;" ::: "memory");
        const uint32_t ra = mapa(sm + OFF_STG + mine, peer), rbar = mapa(bars + BAR_M, peer);
#pragma unroll
        for (int v = 0; v < 4; v++)
          st_async4(ra + v * 512, pack2(M[32 + 8 * v], M[33 + 8 * v]), pack2(M[34 + 8 * v], M[35 + 8 * v]), pack2(M[36 + 8 * v], M[37 + 8 * v]), pack2(M[38 + 8 * v], M[39 + 8 * v]), rbar);
        xr[0] = ldg_nc<0>(p.x + ooff); xr[1] = ldg_nc<16 * DM>(p.x + ooff);
        xr[2] = ldg_nc<64>(p.x + ooff); xr[3] = ldg_nc<16 * DM + 64>(p.x + ooff);
      }
      if (S == S_Y + 3) {
        mbar_wait(bars + BAR_M, 0);
#pragma unroll
        for (int v = 0; v < 4; v++) {
          const uint4 t = lds4u(sm + OFF_STG + mine + v * 512);
          M[8 * v] += bf_lo(t.x); M[8 * v + 1] += bf_hi(t.x); M[8 * v + 2] += bf_lo(t.y); M[8 * v + 3] += bf_hi(t.y);
          M[8 * v + 4] += bf_lo(t.z); M[8 * v + 5] += bf_hi(t.z); M[8 * v + 6] += bf_lo(t.w); M[8 * v + 7] += bf_hi(t.w);
        }
      }
      if (S == S_END - NST + 1 && c.lead) mbar_arrive_cluster(mapa(bars + BAR_OK, peer));
      if constexpr (S >= S_Y + 4) {
        constexpr int G = (S - S_Y - 4) >> 1, H = (S - S_Y - 4) & 1;
        uint32_t w[4];
#pragma unroll
        for (int i = 0; i < 4; i++) {
          const float2 b = lds2f(sm + OFF_B2 + (32 * G + 8 * i) * 4 + (lane & 3) * 8);
          const int r = 4 * (4 * G + i) + 2 * H;
          const float z0 = fmaf(M[r], 0.5f, b.x), z1 = fmaf(M[r + 1], 0.5f, b.y);
          w[i] = pack2(fmaf(z0, tanh_f(z0), z0), fmaf(z1, tanh_f(z1), z1)) ^ sgn;
        }
        const uint32_t tb = sm + OFF_STG + warp * 4096 + (2 * G + H) * 512;
        __syncwarp();
        asm volatile("stmatrix.sync.aligned.m8n8.x4.shared.b16 [%0], {%1,%2,%3,%4};"
                     :: "r"(tb + (lane & 7) * 64 + (((lane >> 3) ^ ((lane >> 1) & 3)) << 4)), "r"(w[0]), "r"(w[1]), "r"(w[2]), "r"(w[3]) : "memory");
        __syncwarp();
        g[2 * G + H] = lds4u(tb + (lane >> 2) * 64 + (((lane & 3) ^ ((lane >> 3) & 3)) << 4));
      }
    });
    mbar_wait(bars + BAR_OK, 0);
    const uint32_t rl_ = mapa(sm + LAND_STAGE * STB + mine, peer), rlb = mapa(bars + BAR_Y, peer);
    TLC(7);
    wg_wait<0>();
    reg_fence(Y);
    TLC(8);
#pragma unroll
    for (int v = 0; v < 4; v++)
      st_async4(rl_ + v * 512, pack2(Y[32 + 8 * v], Y[33 + 8 * v]), pack2(Y[34 + 8 * v], Y[35 + 8 * v]), pack2(Y[36 + 8 * v], Y[37 + 8 * v]), pack2(Y[38 + 8 * v], Y[39 + 8 * v]), rlb);
    mbar_wait(bars + BAR_Y, 0);
    TLC(9);
#pragma unroll
    for (int G = 0; G < 2; G++) {
      uint32_t o0[4], o1[4];
      const uint4 tv[2] = {lds4u(sm + LAND_STAGE * STB + mine + 2 * G * 512), lds4u(sm + LAND_STAGE * STB + mine + (2 * G + 1) * 512)};
      const uint32_t g0[4] = {g[2 * G].x, g[2 * G].y, g[2 * G].z, g[2 * G].w}, g1[4] = {g[2 * G + 1].x, g[2 * G + 1].y, g[2 * G + 1].z, g[2 * G + 1].w};
      const uint32_t x0[4] = {xr[2 * G].x, xr[2 * G].y, xr[2 * G].z, xr[2 * G].w}, x1[4] = {xr[2 * G + 1].x, xr[2 * G + 1].y, xr[2 * G + 1].z, xr[2 * G + 1].w};
#pragma unroll
      for (int i = 0; i < 4; i++) {
        const int a = 4 * (4 * G + i);
        const uint32_t t0 = (i & 1) ? tv[i >> 1].z : tv[i >> 1].x, t1 = (i & 1) ? tv[i >> 1].w : tv[i >> 1].y;
        o0[i] = pack2(fmaf(Y[a] - bf_lo(t0), bf_lo(g0[i]), bf_lo(x0[i])), fmaf(Y[a + 1] - bf_hi(t0), bf_hi(g0[i]), bf_hi(x0[i])));
        o1[i] = pack2(fmaf(Y[a + 2] - bf_lo(t1), bf_lo(g1[i]), bf_lo(x1[i])), fmaf(Y[a + 3] - bf_hi(t1), bf_hi(g1[i]), bf_hi(x1[i])));
      }
      stg4(p.out + ooff + 32 * G, o0[0], o0[1], o0[2], o0[3]);
      stg4(p.out + ooff + 32 * G + 8 * DM, o1[0], o1[1], o1[2], o1[3]);
    }
    TLC(10);
  }
}

typedef CUresult (*EncFn)(CUtensorMap*, CUtensorMapDataType, cuuint32_t, void*, const cuuint64_t*, const cuuint64_t*, const cuuint32_t*,
                          const cuuint32_t*, CUtensorMapInterleave, CUtensorMapSwizzle, CUtensorMapL2promotion, CUtensorMapFloatOOBfill);

void make_map(EncFn enc, CUtensorMap* m, const void* ptr, int nd, const uint64_t* dims, const uint64_t* strides, const uint32_t* box,
              CUtensorMapSwizzle sw = CU_TENSOR_MAP_SWIZZLE_128B) {
  const cuuint32_t es[5] = {1, 1, 1, 1, 1};
  cuuint64_t d[5], s[5]; cuuint32_t b[5];
  for (int i = 0; i < nd; i++) { d[i] = dims[i]; b[i] = box[i]; if (i + 1 < nd) s[i] = strides[i]; }
  enc(m, CU_TENSOR_MAP_DATA_TYPE_BFLOAT16, nd, const_cast<void*>(ptr), d, s, b, es, CU_TENSOR_MAP_INTERLEAVE_NONE,
      sw, CU_TENSOR_MAP_L2_PROMOTION_L2_128B, CU_TENSOR_MAP_FLOAT_OOB_FILL_NONE);
}

}

extern "C" void kernel_launch(void* const* d_in, const int* in_sizes, int n_in, void* d_out, int out_size) {
  static Params prm;
  static const void* key[11];
  static EncFn enc = nullptr;
  bool same = enc != nullptr && key[10] == d_out;
  for (int i = 0; i < 10 && same; i++) same = key[i] == d_in[i];
  if (!same) {
    if (!enc) {
      cudaDriverEntryPointQueryResult q;
      cudaGetDriverEntryPoint("cuTensorMapEncodeTiled", reinterpret_cast<void**>(&enc), cudaEnableDefault, &q);
      cudaFuncSetAttribute(fused_kernel, cudaFuncAttributeMaxDynamicSharedMemorySize, SMEM_BYTES);
    }
    void *xn, *uv, *h;
    cudaGetSymbolAddress(&xn, g_xn);
    cudaGetSymbolAddress(&uv, g_uv);
    cudaGetSymbolAddress(&h, g_h);
    const uint64_t R = DM * 2;
    const uint32_t box2[2] = {64, 128}, box3[3] = {64, 64, 2}, box5[5] = {64, 2, 4, 4, 2}, boxs[2] = {32, 128};
    { const uint64_t d[2] = {DM, SEQ}, s[1] = {R}; make_map(enc, &prm.mx, d_in[0], 2, d, s, box2); }
    { const uint64_t d[2] = {64, SEQ * 8}, s[1] = {128}; make_map(enc, &prm.mx16, d_in[0], 2, d, s, box2); make_map(enc, &prm.sxn, xn, 2, d, s, box2); }
    { const uint64_t d[3] = {64, SEQ, 8}, s[2] = {R, 128}; make_map(enc, &prm.mxn, xn, 3, d, s, box3); }
    { const uint64_t d[2] = {SEQ, SEQ}, s[1] = {SEQ * 2}; make_map(enc, &prm.mcr, d_in[1], 2, d, s, box2); make_map(enc, &prm.mci, d_in[2], 2, d, s, box2); }
    { const uint64_t d[5] = {DM, 2, 4, 4, DM / 32}, s[4] = {R, 8 * R, 2 * R, 32 * R};
      make_map(enc, &prm.mdre, d_in[3], 5, d, s, box5); make_map(enc, &prm.mdim, d_in[4], 5, d, s, box5); }
    { const uint64_t d[3] = {FF, DM, 2}, s[2] = {FF * 2, 128}; make_map(enc, &prm.mw1, d_in[6], 3, d, s, box3); }
    { const uint64_t d[2] = {FF, SEQ}, s[1] = {FF * 2}; make_map(enc, &prm.mh, h, 2, d, s, box2); make_map(enc, &prm.sh, h, 2, d, s, boxs, CU_TENSOR_MAP_SWIZZLE_NONE); }
    { const uint64_t d[5] = {DM, 2, 4, 4, FF / 32}, s[4] = {R, 8 * R, 2 * R, 32 * R}; make_map(enc, &prm.mw2, d_in[8], 5, d, s, box5); }
    { const uint64_t d[2] = {DM, 2 * SEQ}, s[1] = {R}; make_map(enc, &prm.muv, uv, 2, d, s, box2); make_map(enc, &prm.suv, uv, 2, d, s, boxs, CU_TENSOR_MAP_SWIZZLE_NONE); }
    prm.x = (const __nv_bfloat16*)d_in[0]; prm.w1 = (const __nv_bfloat16*)d_in[6]; prm.b1 = (const __nv_bfloat16*)d_in[7];
    prm.cr = (const __nv_bfloat16*)d_in[1]; prm.ci = (const __nv_bfloat16*)d_in[2]; prm.dre = (const __nv_bfloat16*)d_in[3];
    prm.dim = (const __nv_bfloat16*)d_in[4]; prm.w2 = (const __nv_bfloat16*)d_in[8];
    prm.b2 = (const __nv_bfloat16*)d_in[9]; prm.out = (__nv_bfloat16*)d_out;
    for (int i = 0; i < 10; i++) key[i] = d_in[i];
    key[10] = d_out;
  }
  fused_kernel<<<128, 384, SMEM_BYTES>>>(prm);
}
```

```cpp
#include <cuda_runtime.h>
#include <cuda_bf16.h>
#include <cuda.h>
#include <stdint.h>

namespace {

constexpr int SEQ = 2048, DM = 512, FF = 1792;
constexpr int NST = 6;
constexpr int STB = 32768;
constexpr int OFF_STG = NST * STB;
constexpr int OFF_VH = OFF_STG + 32768;
constexpr int OFF_B2 = OFF_VH + 1792;
constexpr int OFF_BAR = OFF_B2 + 256;
constexpr int SMEM_BYTES = OFF_BAR + 408;
constexpr int OFF_ST = OFF_STG + 8192;
static_assert(SMEM_BYTES <= 232448, "smem");
constexpr int BAR_FULL = 0, BAR_EMPTY = 48, BAR_XF = 96, BAR_BF = 160, BAR_BE = 336, BAR_V = 232, BAR_FREE = 304,
              BAR_E = 248, BAR_M = 256, BAR_Y = 264, BAR_OK = 272, BAR_DEP = 280, OFF_EPOCH = 288, BAR_HI = 200, BAR_HD = 208, BAR_V2 = 216, BAR_Y1 = 240, BAR_DU = 376;
__host__ __device__ constexpr int xslot(int k) { return (k < 4 ? k : 2 * k - 4) * 16384; }
constexpr int NB1 = 5;
__host__ __device__ constexpr int bslot(int i) { return i == 0 ? 11 * 16384 : i == 4 ? OFF_STG + 16384 : (3 + 2 * i) * 16384; }
constexpr int S_S = 16, S_M = 48, S_Y = 62, S_END = 70;
__host__ __device__ constexpr int stage_of(int s) { return (s - S_S) % NST; }
__host__ __device__ constexpr int par_of(int s) { return ((s - S_S) / NST) & 1; }
constexpr int LAND_STAGE = stage_of(S_END - NST);
constexpr int HS0 = 12;
__host__ __device__ constexpr int xn_gap(int i) { return i == 0 ? 7 : i < 3 ? 8 : i == 3 ? 9 : i < 15 ? 15 : 19; }
__host__ __device__ constexpr int hvec(int u) { return (u < 16 ? 48 + 4 * u : 4 * (u - 16)) * 16; }
constexpr int S_ROLL = HS0 + 28;
constexpr int GW = 4;

constexpr int C_DONE = 0, C_XN = 1, C_H = 2, C_UV = 8;

struct Params {
  const __nv_bfloat16 *x, *b1, *b2;
  __nv_bfloat16* out;
  float4* stats;
  float4* cs;
  unsigned* cnt;
  CUtensorMap mw1s, mw1h, mx, sxn, mxn, mw1, mcr, mci, mh, sh, mw2, muv, suv, mdre, mdim;
};

__device__ __align__(1024) __nv_bfloat16 g_xn[SEQ * DM];
__device__ __align__(1024) __nv_bfloat16 g_uv[2 * SEQ * DM];
__device__ __align__(1024) __nv_bfloat16 g_h[SEQ * FF];
__device__ __align__(128) float4 g_stats[SEQ];
__device__ __align__(128) float4 g_cs[2][8][96];
__device__ __align__(128) unsigned g_cnt[16 * 32];

__device__ __forceinline__ void mbar_init(uint32_t bar, uint32_t cnt) { asm volatile("mbarrier.init.shared::cta.b64 [%0], %1;" :: "r"(bar), "r"(cnt) : "memory"); }
__device__ __forceinline__ void mbar_expect_tx(uint32_t bar, uint32_t bytes) { asm volatile("mbarrier.arrive.expect_tx.shared::cta.b64 _, [%0], %1;" :: "r"(bar), "r"(bytes) : "memory"); }
__device__ __forceinline__ void mbar_arrive(uint32_t bar) { asm volatile("mbarrier.arrive.shared::cta.b64 _, [%0];" :: "r"(bar) : "memory"); }
__device__ __forceinline__ void mbar_arrive_cluster(uint32_t remote_bar) { asm volatile("mbarrier.arrive.shared::cluster.b64 _, [%0];" :: "r"(remote_bar) : "memory"); }
__device__ __forceinline__ uint32_t mapa(uint32_t addr, uint32_t cta) { uint32_t r; asm("mapa.shared::cluster.u32 %0, %1, %2;" : "=r"(r) : "r"(addr), "r"(cta)); return r; }
__device__ __forceinline__ bool mbar_try(uint32_t bar, uint32_t parity) {
  uint32_t ok;
  asm volatile("{\n.reg .pred p;\nmbarrier.try_wait.parity.shared::cta.b64 p, [%1], %2;\nselp.u32 %0, 1, 0, p;\n}" : "=r"(ok) : "r"(bar), "r"(parity) : "memory");
  return ok;
}
__device__ __forceinline__ void mbar_wait(uint32_t bar, uint32_t parity) {
  if (mbar_try(bar, parity)) return;
  const uint32_t t0 = (uint32_t)clock();
  while (!mbar_try(bar, parity) && (uint32_t)clock() - t0 < (1u << 25)) {}
}
__device__ __forceinline__ void mbar_block(uint32_t bar, uint32_t parity) {
  for (int n = 0; n < 4096; n++) if (mbar_try(bar, parity)) break;
}
__device__ __forceinline__ bool elect_one() {
  uint32_t p;
  asm volatile("{\n.reg .pred p;\nelect.sync _|p, 0xffffffff;\nselp.u32 %0, 1, 0, p;\n}" : "=r"(p));
  return p;
}
__device__ __forceinline__ void tma2d(uint32_t dst, const CUtensorMap* m, int c0, int c1, uint32_t bar) {
  asm volatile("cp.async.bulk.tensor.2d.shared::cluster.global.mbarrier::complete_tx::bytes [%0], [%1, {%3, %4}], [%2];"
    :: "r"(dst), "l"(m), "r"(bar), "r"(c0), "r"(c1) : "memory");
}
__device__ __forceinline__ void tma3d(uint32_t dst, const CUtensorMap* m, int c0, int c1, int c2, uint32_t bar) {
  asm volatile("cp.async.bulk.tensor.3d.shared::cluster.global.mbarrier::complete_tx::bytes [%0], [%1, {%3, %4, %5}], [%2];"
    :: "r"(dst), "l"(m), "r"(bar), "r"(c0), "r"(c1), "r"(c2) : "memory");
}
__device__ __forceinline__ void tma5d(uint32_t dst, const CUtensorMap* m, int c0, int c4, uint32_t bar) {
  asm volatile("cp.async.bulk.tensor.5d.shared::cluster.global.mbarrier::complete_tx::bytes [%0], [%1, {%3, %5, %5, %5, %4}], [%2];"
    :: "r"(dst), "l"(m), "r"(bar), "r"(c0), "r"(c4), "r"(0) : "memory");
}
__device__ __forceinline__ void wg_fence() { asm volatile("wgmma.fence.sync.aligned;" ::: "memory"); }
__device__ __forceinline__ void wg_commit() { asm volatile("wgmma.commit_group.sync.aligned;" ::: "memory"); }
template <int N> __device__ __forceinline__ void wg_wait() { asm volatile("wgmma.wait_group.sync.aligned %0;" :: "n"(N) : "memory"); }
template <int N> __device__ __forceinline__ void reg_fence(float (&d)[N]) {
#pragma unroll
  for (int i = 0; i < N; i++) asm volatile("" : "+f"(d[i]) :: "memory");
}
template <int AO, int BO> __device__ __forceinline__ void wgmma_n128_tb0(float* d, uint32_t a, uint32_t b, int scale_d) {
  asm volatile("{\n.reg .pred p;\n.reg .b32 la, lb, hi, hj;\n.reg .b64 da, db;\nsetp.ne.b32 p, %66, 0;\nmov.b32 hi, 0x40000040;\nmov.b32 hj, 0x40000040;\n"
    "add.u32 la, %64, %67;\nadd.u32 lb, %65, %68;\nmov.b64 da, {la, hi};\nmov.b64 db, {lb, hj};\n"
    "wgmma.mma_async.sync.aligned.m64n128k16.f32.bf16.bf16 "
    "{%0, %1, %2, %3, %4, %5, %6, %7, %8, %9, %10, %11, %12, %13, %14, %15, %16, %17, %18, %19, %20, %21, %22, %23, %24, %25, %26, %27, %28, %29, %30, %31, %32, %33, %34, %35, %36, %37, %38, %39, %40, %41, %42, %43, %44, %45, %46, %47, %48, %49, %50, %51, %52, %53, %54, %55, %56, %57, %58, %59, %60, %61, %62, %63}, "
    "da, db, p, 1, 1, 0, 0;\n}\n"
    : "+f"(d[0]), "+f"(d[1]), "+f"(d[2]), "+f"(d[3]), "+f"(d[4]), "+f"(d[5]), "+f"(d[6]), "+f"(d[7]), "+f"(d[8]), "+f"(d[9]), "+f"(d[10]), "+f"(d[11]), "+f"(d[12]), "+f"(d[13]), "+f"(d[14]), "+f"(d[15]), "+f"(d[16]), "+f"(d[17]), "+f"(d[18]), "+f"(d[19]), "+f"(d[20]), "+f"(d[21]), "+f"(d[22]), "+f"(d[23]), "+f"(d[24]), "+f"(d[25]), "+f"(d[26]), "+f"(d[27]), "+f"(d[28]), "+f"(d[29]), "+f"(d[30]), "+f"(d[31]), "+f"(d[32]), "+f"(d[33]), "+f"(d[34]), "+f"(d[35]), "+f"(d[36]), "+f"(d[37]), "+f"(d[38]), "+f"(d[39]), "+f"(d[40]), "+f"(d[41]), "+f"(d[42]), "+f"(d[43]), "+f"(d[44]), "+f"(d[45]), "+f"(d[46]), "+f"(d[47]), "+f"(d[48]), "+f"(d[49]), "+f"(d[50]), "+f"(d[51]), "+f"(d[52]), "+f"(d[53]), "+f"(d[54]), "+f"(d[55]), "+f"(d[56]), "+f"(d[57]), "+f"(d[58]), "+f"(d[59]), "+f"(d[60]), "+f"(d[61]), "+f"(d[62]), "+f"(d[63])
    : "r"(a), "r"(b), "r"(scale_d), "n"(AO), "n"(BO));
}
template <int AO, int BO> __device__ __forceinline__ void wgmma_n128_tb1(float* d, uint32_t a, uint32_t b, int scale_d) {
  asm volatile("{\n.reg .pred p;\n.reg .b32 la, lb, hi, hj;\n.reg .b64 da, db;\nsetp.ne.b32 p, %66, 0;\nmov.b32 hi, 0x40000040;\nmov.b32 hj, 0x40000040;\n"
    "add.u32 la, %64, %67;\nadd.u32 lb, %65, %68;\nmov.b64 da, {la, hi};\nmov.b64 db, {lb, hj};\n"
    "wgmma.mma_async.sync.aligned.m64n128k16.f32.bf16.bf16 "
    "{%0, %1, %2, %3, %4, %5, %6, %7, %8, %9, %10, %11, %12, %13, %14, %15, %16, %17, %18, %19, %20, %21, %22, %23, %24, %25, %26, %27, %28, %29, %30, %31, %32, %33, %34, %35, %36, %37, %38, %39, %40, %41, %42, %43, %44, %45, %46, %47, %48, %49, %50, %51, %52, %53, %54, %55, %56, %57, %58, %59, %60, %61, %62, %63}, "
    "da, db, p, 1, 1, 0, 1;\n}\n"
    : "+f"(d[0]), "+f"(d[1]), "+f"(d[2]), "+f"(d[3]), "+f"(d[4]), "+f"(d[5]), "+f"(d[6]), "+f"(d[7]), "+f"(d[8]), "+f"(d[9]), "+f"(d[10]), "+f"(d[11]), "+f"(d[12]), "+f"(d[13]), "+f"(d[14]), "+f"(d[15]), "+f"(d[16]), "+f"(d[17]), "+f"(d[18]), "+f"(d[19]), "+f"(d[20]), "+f"(d[21]), "+f"(d[22]), "+f"(d[23]), "+f"(d[24]), "+f"(d[25]), "+f"(d[26]), "+f"(d[27]), "+f"(d[28]), "+f"(d[29]), "+f"(d[30]), "+f"(d[31]), "+f"(d[32]), "+f"(d[33]), "+f"(d[34]), "+f"(d[35]), "+f"(d[36]), "+f"(d[37]), "+f"(d[38]), "+f"(d[39]), "+f"(d[40]), "+f"(d[41]), "+f"(d[42]), "+f"(d[43]), "+f"(d[44]), "+f"(d[45]), "+f"(d[46]), "+f"(d[47]), "+f"(d[48]), "+f"(d[49]), "+f"(d[50]), "+f"(d[51]), "+f"(d[52]), "+f"(d[53]), "+f"(d[54]), "+f"(d[55]), "+f"(d[56]), "+f"(d[57]), "+f"(d[58]), "+f"(d[59]), "+f"(d[60]), "+f"(d[61]), "+f"(d[62]), "+f"(d[63])
    : "r"(a), "r"(b), "r"(scale_d), "n"(AO), "n"(BO));
}
template <int AO, int BO> __device__ __forceinline__ void wgmma_n96_tb1(float* d, uint32_t a, uint32_t b, int scale_d) {
  asm volatile("{\n.reg .pred p;\n.reg .b32 la, lb, hi, hj;\n.reg .b64 da, db;\nsetp.ne.b32 p, %50, 0;\nmov.b32 hi, 0x40000040;\nmov.b32 hj, 0x40000040;\n"
    "add.u32 la, %48, %51;\nadd.u32 lb, %49, %52;\nmov.b64 da, {la, hi};\nmov.b64 db, {lb, hj};\n"
    "wgmma.mma_async.sync.aligned.m64n96k16.f32.bf16.bf16 "
    "{%0, %1, %2, %3, %4, %5, %6, %7, %8, %9, %10, %11, %12, %13, %14, %15, %16, %17, %18, %19, %20, %21, %22, %23, %24, %25, %26, %27, %28, %29, %30, %31, %32, %33, %34, %35, %36, %37, %38, %39, %40, %41, %42, %43, %44, %45, %46, %47}, "
    "da, db, p, 1, 1, 0, 1;\n}\n"
    : "+f"(d[0]), "+f"(d[1]), "+f"(d[2]), "+f"(d[3]), "+f"(d[4]), "+f"(d[5]), "+f"(d[6]), "+f"(d[7]), "+f"(d[8]), "+f"(d[9]), "+f"(d[10]), "+f"(d[11]), "+f"(d[12]), "+f"(d[13]), "+f"(d[14]), "+f"(d[15]), "+f"(d[16]), "+f"(d[17]), "+f"(d[18]), "+f"(d[19]), "+f"(d[20]), "+f"(d[21]), "+f"(d[22]), "+f"(d[23]), "+f"(d[24]), "+f"(d[25]), "+f"(d[26]), "+f"(d[27]), "+f"(d[28]), "+f"(d[29]), "+f"(d[30]), "+f"(d[31]), "+f"(d[32]), "+f"(d[33]), "+f"(d[34]), "+f"(d[35]), "+f"(d[36]), "+f"(d[37]), "+f"(d[38]), "+f"(d[39]), "+f"(d[40]), "+f"(d[41]), "+f"(d[42]), "+f"(d[43]), "+f"(d[44]), "+f"(d[45]), "+f"(d[46]), "+f"(d[47])
    : "r"(a), "r"(b), "r"(scale_d), "n"(AO), "n"(BO));
}

__device__ __forceinline__ void bar_arrive(int id, int n) { asm volatile("bar.arrive %0, %1;" :: "r"(id), "r"(n) : "memory"); }
__device__ __forceinline__ void bar_sync(int id, int n) { asm volatile("bar.sync %0, %1;" :: "r"(id), "r"(n) : "memory"); }
__device__ __forceinline__ unsigned ld_rlx(const unsigned* p) { unsigned v; asm volatile("ld.relaxed.gpu.global.u32 %0, [%1];" : "=r"(v) : "l"(p) : "memory"); return v; }
__device__ __forceinline__ void red_add(unsigned* p) { asm volatile("red.relaxed.gpu.global.add.u32 [%0], 1;" :: "l"(p) : "memory"); }
__device__ __forceinline__ void wait_cnt(const unsigned* p, unsigned target) {
  for (uint32_t n = 0; n < (1u << 16); n++) if ((int)(ld_rlx(p) - target) >= 0) break;
}
__device__ __forceinline__ float bf_lo(uint32_t v) { return __uint_as_float(v << 16); }
__device__ __forceinline__ float bf_hi(uint32_t v) { return __uint_as_float(v & 0xffff0000u); }
__device__ __forceinline__ uint32_t pack2(float lo, float hi) { uint32_t r; asm("cvt.rn.bf16x2.f32 %0, %1, %2;" : "=r"(r) : "f"(hi), "f"(lo)); return r; }
__device__ __forceinline__ uint32_t pack2v(float lo, float hi) { uint32_t r; asm volatile("cvt.rn.bf16x2.f32 %0, %1, %2;" : "=r"(r) : "f"(hi), "f"(lo)); return r; }
__device__ __forceinline__ float bfr(float v) { return bf_hi(pack2(0.f, v)); }
__device__ __forceinline__ uint32_t tagf(float v, uint32_t tag) { return (__float_as_uint(v) & ~3u) | tag; }
template <int OFF> __device__ __forceinline__ uint4 ld_msg(const void* p) { uint4 v; asm volatile("ld.relaxed.gpu.global.v4.u32 {%0,%1,%2,%3}, [%4 + %5];" : "=r"(v.x), "=r"(v.y), "=r"(v.z), "=r"(v.w) : "l"(p), "n"(OFF) : "memory"); return v; }
__device__ __forceinline__ void sts4(uint32_t a, uint32_t x, uint32_t y, uint32_t z, uint32_t w) { asm volatile("st.shared.v4.u32 [%0], {%1,%2,%3,%4};" :: "r"(a), "r"(x), "r"(y), "r"(z), "r"(w) : "memory"); }
__device__ __forceinline__ void tma_st2d(const CUtensorMap* m, uint32_t src, int c0, int c1) {
  asm volatile("cp.async.bulk.tensor.2d.global.shared::cta.bulk_group [%0, {%2, %3}], [%1];" :: "l"(m), "r"(src), "r"(c0), "r"(c1) : "memory");
}
__device__ __forceinline__ float rcp_f(float v) { float r; asm("rcp.approx.ftz.f32 %0, %1;" : "=f"(r) : "f"(v)); return r; }
__device__ __forceinline__ float sqrt_f(float v) { float r; asm("sqrt.approx.ftz.f32 %0, %1;" : "=f"(r) : "f"(v)); return r; }
__device__ __forceinline__ float tanh_f(float v) { float r; asm("tanh.approx.f32 %0, %1;" : "=f"(r) : "f"(v)); return r; }
__device__ __forceinline__ float gelu_half(float hf) {
  const float k0 = 2.0f * 0.7978845608028654f, k1 = 8.0f * 0.7978845608028654f * 0.044715f;
  return fmaf(hf, tanh_f(hf * fmaf(hf * hf, k1, k0)), hf);
}
__device__ __forceinline__ uint2 ld_msg2(const void* p) { uint2 v; asm volatile("ld.relaxed.gpu.global.v2.u32 {%0,%1}, [%2];" : "=r"(v.x), "=r"(v.y) : "l"(p) : "memory"); return v; }
__device__ __forceinline__ void fence_async_smem() { asm volatile("fence.proxy.async.shared::cta;" ::: "memory"); }
template <int OFF> __device__ __forceinline__ uint4 ldg_nc(const void* p) { uint4 v; asm volatile("ld.global.nc.v4.u32 {%0,%1,%2,%3}, [%4 + %5];" : "=r"(v.x), "=r"(v.y), "=r"(v.z), "=r"(v.w) : "l"(p), "n"(OFF)); return v; }
__device__ __forceinline__ void stg4(void* p, uint32_t a, uint32_t b, uint32_t c, uint32_t d) { asm volatile("st.global.v4.u32 [%0], {%1,%2,%3,%4};" :: "l"(p), "r"(a), "r"(b), "r"(c), "r"(d) : "memory"); }
__device__ __forceinline__ float4 lds4f(uint32_t a) { float4 v; asm volatile("ld.shared.v4.f32 {%0,%1,%2,%3}, [%4];" : "=f"(v.x), "=f"(v.y), "=f"(v.z), "=f"(v.w) : "r"(a)); return v; }
__device__ __forceinline__ uint4 lds4u(uint32_t a) { uint4 v; asm volatile("ld.shared.v4.u32 {%0,%1,%2,%3}, [%4];" : "=r"(v.x), "=r"(v.y), "=r"(v.z), "=r"(v.w) : "r"(a) : "memory"); return v; }
__device__ __forceinline__ float2 lds2f(uint32_t a) { float2 v; asm volatile("ld.shared.v2.f32 {%0,%1}, [%2];" : "=f"(v.x), "=f"(v.y) : "r"(a)); return v; }
__device__ __forceinline__ void st_async4(uint32_t raddr, uint32_t a, uint32_t b, uint32_t c, uint32_t d, uint32_t rbar) {
  asm volatile("st.async.weak.shared::cluster.mbarrier::complete_tx::bytes.v4.b32 [%0], {%1,%2,%3,%4}, [%5];"
    :: "r"(raddr), "r"(a), "r"(b), "r"(c), "r"(d), "r"(rbar) : "memory");
}

struct Ctx {
  uint32_t sm;
  uint32_t da;
  uint32_t db;
  uint32_t lbo96;
  bool lead;
};
template <int V> struct IC { static constexpr int value = V; };
template <int S0, int S1, class F>
__device__ __forceinline__ void static_for(F&& f) {
  if constexpr (S0 < S1) { f(IC<S0>{}); static_for<S0 + 1, S1>(f); }
}
template <int N, int TB, int WP, class F>
__device__ __forceinline__ void mma_issue(float (&acc)[N / 2], const Ctx& c, uint32_t offa, uint32_t offb, int accum, F&& f) {
  const uint32_t a = c.da + (offa >> 4), b = c.db + (offb >> 4) + (N == 96 ? c.lbo96 : TB ? (512u << 16) : (1u << 16));
  wg_fence();
  static_for<0, 4>([&](auto K_) {
    constexpr int K = decltype(K_)::value, BO = K * (TB ? 128 : 2);
    if constexpr (N == 128 && TB == 0) wgmma_n128_tb0<2 * K, BO>(acc, a, b, K ? 1 : accum);
    if constexpr (N == 128 && TB == 1) wgmma_n128_tb1<2 * K, BO>(acc, a, b, K ? 1 : accum);
    if constexpr (N == 96) wgmma_n96_tb1<2 * K, BO>(acc, a, b, K ? 1 : accum);
    if constexpr (K == WP && K < 3) { wg_wait<0>(); f(IC<4>{}); }
    if constexpr (K < 3) f(K_);
  });
  wg_commit();
  if constexpr (WP == 3) { wg_wait<1>(); f(IC<4>{}); }
}
template <int N, int S, class F>
__device__ __forceinline__ void step1(float (&acc)[N / 2], const Ctx& c, F&& f) {
  if (S < 8) mbar_wait(c.sm + OFF_BAR + BAR_XF + 8 * S, 0);
  mbar_wait(c.sm + OFF_BAR + BAR_BF + 8 * (S % NB1), (S / NB1) & 1);
  mma_issue<N, 1, 3>(acc, c, xslot(S & 7), bslot(S % NB1), (S & 7) != 0, f);
}
template <int TB, int WP = 3, class F>
__device__ __forceinline__ void step2(float (&acc)[64], Ctx& c, int st, uint32_t ph, int accum, F&& f) {
  mbar_wait(c.sm + OFF_BAR + BAR_FULL + 8 * st, ph);
  mma_issue<128, TB, WP>(acc, c, st * STB, st * STB + 16384, accum, f);
}
__device__ __forceinline__ void release2(const Ctx& c, int st) {
  if (c.lead) mbar_arrive(c.sm + OFF_BAR + BAR_EMPTY + 8 * st);
}
template <int S>
__device__ __forceinline__ void release(const Ctx& c) {
  if constexpr (S < S_S) {
    if (c.lead) {
      if constexpr (S + NB1 < S_S) mbar_arrive(c.sm + OFF_BAR + BAR_BE + 8 * (S % NB1));
      if constexpr (S == 9) mbar_arrive(c.sm + OFF_BAR + BAR_EMPTY);
      if constexpr (S >= 11) mbar_arrive(c.sm + OFF_BAR + BAR_EMPTY + 8 * (S - 10));
    }
  } else if constexpr (S < S_END - NST) {
    release2(c, stage_of(S));
  }
}

struct HEpi { float a0, b0, a1, b1; uint32_t vec, stg, never; uint32_t w0[4], w1[4]; };
template <int G, int I, int NA>
__device__ __forceinline__ void h_unit(const float (&acc)[NA], HEpi& e, const float4 v) {
  const int r = 4 * (4 * G + I);
  e.w0[I] = pack2v(gelu_half(fmaf(e.a0, acc[r], fmaf(e.b0, v.x, v.z))), gelu_half(fmaf(e.a0, acc[r + 1], fmaf(e.b0, v.y, v.w))));
  e.w1[I] = pack2v(gelu_half(fmaf(e.a1, acc[r + 2], fmaf(e.b1, v.x, v.z))), gelu_half(fmaf(e.a1, acc[r + 3], fmaf(e.b1, v.y, v.w))));
  asm volatile("{\n.reg .pred p;\nsetp.ne.u32 p, %0, 0;\n@p st.shared.v2.u32 [%1], {%2, %3};\n}" :: "r"(e.never), "r"(e.stg), "r"(e.w0[I]), "r"(e.w1[I]) : "memory");
}
template <int G>
__device__ __forceinline__ void h_store(HEpi& e, int bar_id) {
  sts4(e.stg + G * 8192, e.w0[0], e.w0[1], e.w0[2], e.w0[3]);
  sts4(e.stg + G * 8192 + 512, e.w1[0], e.w1[1], e.w1[2], e.w1[3]);
  bar_arrive(bar_id, 288);
}

__global__ void __cluster_dims__(2, 1, 1) __launch_bounds__(384, 1) fused_kernel(const __grid_constant__ Params p) {
  extern __shared__ __align__(1024) uint8_t smem_raw[];
  const uint32_t sm = (uint32_t)__cvta_generic_to_shared(smem_raw);
  if (threadIdx.x == 0) {
    asm volatile("prefetch.tensormap [%0];" :: "l"(&p.mx) : "memory");
    asm volatile("prefetch.tensormap [%0];" :: "l"(&p.mw1) : "memory");
  }
  const int tid = threadIdx.x, lane = tid & 31;
  const int warp = __shfl_sync(0xffffffffu, tid >> 5, 0);
  int lc;
  {
    const int c = blockIdx.x >> 1;
    if (c < 4) lc = 4 + c;
    else if (c < 36) lc = ((c - 4) & 7) * 8 + ((c - 4) >> 3);
    else lc = (1 + (c - 36) % 7) * 8 + 4 + (c - 36) / 7;
  }
  const int rk = blockIdx.x & 1, cb = lc & 3, rb = lc >> 2, j = cb * 2 + rk;
  const int row0 = rb * 128;
  const int colq = cb * 448 + rk * 320, colr = cb * 448 + 128 + rk * 128, colh = cb * 448 + 192;
  const uint32_t bars = sm + OFF_BAR;
#define EPOCH() mbar_wait(bars + BAR_E, 0); unsigned epoch; asm volatile("ld.shared.u32 %0, [%1];" : "=r"(epoch) : "r"(bars + OFF_EPOCH) : "memory"); const uint32_t tag = epoch & 3
  if (tid >= 256) asm volatile("setmaxnreg.dec.sync.aligned.u32 104;");
  if (tid >= 256 && tid < 288) {
    uint32_t t0 = 0;
    if (elect_one()) {
      mbar_init(bars + BAR_XF, 1); mbar_init(bars + BAR_BF, 1);
      asm volatile("fence.mbarrier_init.release.cluster;" ::: "memory");
      mbar_expect_tx(bars + BAR_XF, 16384);
      tma2d(sm + xslot(0), &p.mx, 0, row0, bars + BAR_XF);
      mbar_expect_tx(bars + BAR_BF, 16384);
      tma3d(sm + bslot(0), &p.mw1, colq, 0, 0, bars + BAR_BF);
      t0 = clock();
      for (int s = 1; s < 8; s++) mbar_init(bars + BAR_XF + 8 * s, 1);
      for (int s = 0; s < NB1; s++) { if (s) mbar_init(bars + BAR_BF + 8 * s, 1); mbar_init(bars + BAR_BE + 8 * s, 9); }
      mbar_init(bars + BAR_HI, 1);
      asm volatile("fence.mbarrier_init.release.cluster;" ::: "memory");
    }
    __syncwarp();
    bar_arrive(0, 384);
    asm volatile("barrier.cluster.arrive.relaxed.aligned;" ::: "memory");
    if (elect_one()) {
      mbar_arrive(bars + (rb < 2 ? BAR_HI : BAR_BE));
#pragma unroll 1
      for (int k = 1; k < NB1; k++) {
        while ((uint32_t)clock() - t0 < k * 250u) {}
#pragma unroll 1
        for (int kx = k == 1 ? 1 : 2 * k - 2; kx < 2 * k; kx++) {
          mbar_expect_tx(bars + BAR_XF + 8 * kx, 16384);
          tma2d(sm + xslot(kx), &p.mx, kx * 64, row0, bars + BAR_XF + 8 * kx);
        }
        mbar_expect_tx(bars + BAR_BF + 8 * k, 16384);
        tma3d(sm + bslot(k), &p.mw1, colq, k * 64, 0, bars + BAR_BF + 8 * k);
        mbar_arrive(bars + (k == (rb >> 1) ? BAR_HI : BAR_BE + 8 * k));
      }
    }
    __syncwarp();
  }
  if (tid < 32) {
    if (elect_one()) {
      for (int s = 0; s < NST; s++) { mbar_init(bars + BAR_FULL + 8 * s, 1); mbar_init(bars + BAR_EMPTY + 8 * s, 8); }
      for (int s = 0; s < 4; s++) { mbar_init(bars + BAR_FREE + 8 * s, 1); mbar_init(bars + BAR_DU + 8 * s, 1); }
      mbar_init(bars + BAR_V, 2); mbar_init(bars + BAR_V2, 1); mbar_init(bars + BAR_HD, 1); mbar_init(bars + BAR_E, 1);
      mbar_init(bars + BAR_DEP, 1); mbar_init(bars + BAR_M, 1); mbar_init(bars + BAR_Y, 1); mbar_init(bars + BAR_Y1, 1); mbar_init(bars + BAR_OK, 8);
      asm volatile("fence.mbarrier_init.release.cluster;" ::: "memory");
      fence_async_smem();
      mbar_expect_tx(bars + BAR_M, 16384);
      mbar_expect_tx(bars + BAR_Y, 8192);
      mbar_expect_tx(bars + BAR_Y1, 8192);
    }
    __syncwarp();
  }
  if (tid < 256 || tid >= 288) {
    bar_sync(0, 384);
    asm volatile("barrier.cluster.arrive.relaxed.aligned;" ::: "memory");
  }
  if (warp != 8) {
  if (warp > 8) {
    if (warp == 9) {
      unsigned done0 = 0;
      if (lane == 0) done0 = ld_rlx(&p.cnt[rb * 32 + C_DONE]);
      const unsigned epoch = __shfl_sync(0xffffffffu, (done0 >> 3) + 1, 0);
      if (lane == 0) {
        asm volatile("st.shared.u32 [%0], %1;" :: "r"(bars + OFF_EPOCH), "r"(epoch) : "memory");
        mbar_arrive(bars + BAR_E);
        asm volatile("prefetch.tensormap [%0];" :: "l"(&p.sxn) : "memory");
        asm volatile("prefetch.tensormap [%0];" :: "l"(&p.mw1s) : "memory");
        asm volatile("prefetch.tensormap [%0];" :: "l"(&p.sh) : "memory");
        asm volatile("prefetch.tensormap [%0];" :: "l"(&p.suv) : "memory");
      }
#pragma unroll 1
      for (int ev = 0; ev < 12; ev++) {
        bar_sync(1 + (ev & 3), 288);
        if (lane == 0) {
          fence_async_smem();
          const int g = ev < 5 ? ev - 1 : ev < 8 ? ev - 5 : ev - 8;
          if (ev == 0) tma_st2d(&p.sxn, sm + OFF_STG, 0, (row0 + j * 16) * 8);
          else if (ev < 8) tma_st2d(&p.sh, sm + OFF_STG + g * 8192, ev < 5 ? colq + g * 32 : ev < 7 ? colr + g * 32 : colh + rk * 32, row0);
          else tma_st2d(&p.suv, sm + OFF_STG + g * 8192, cb * 128 + g * 32, rk * SEQ + row0);
          asm volatile("cp.async.bulk.commit_group;" ::: "memory");
          if (ev < 10) {
            asm volatile("cp.async.bulk.wait_group.read 0;" ::: "memory");
            if (ev == 0) { mbar_arrive(bars + BAR_FREE); mbar_arrive(bars + BAR_FREE + 8); }
            else mbar_arrive(bars + BAR_FREE + 8 * g);
          }
          if ((0x881 >> ev) & 1) {
            unsigned* cnt = &p.cnt[rb * 32 + (ev == 0 ? C_XN : ev == 11 ? C_UV + rk * 4 + cb : C_H)];
            asm volatile("cp.async.bulk.wait_group 0;" ::: "memory");
            red_add(cnt);
          }
        }
        __syncwarp();
        if ((0x81 >> ev) & 1) {
          const unsigned* cnt = &p.cnt[ev == 0 ? (lane & 15) * 32 + C_XN : rb * 32 + C_H];
          for (uint32_t n = 0; n < (1u << 16); n++)
            if (__all_sync(0xffffffffu, lane >= (ev == 0 ? 16 : 1) || (int)(ld_rlx(cnt) - 8 * epoch) >= 0)) break;
          if (lane == 0) { mbar_arrive(bars + BAR_DEP); }
        }
      }
      if (lane == 0) {
        const unsigned* f = &p.cnt[rb * 32 + C_UV + rk * 4];
        uint32_t todo = 15;
        auto take = [&](const uint4& v) {
          const uint32_t w[4] = {v.x, v.y, v.z, v.w};
#pragma unroll
          for (int i = 0; i < 4; i++)
            if ((todo >> i & 1) && (int)(w[i] - epoch) >= 0) { todo &= ~(1u << i); mbar_arrive(bars + BAR_DU + 8 * i); }
        };
        uint4 v0 = ld_msg<0>(f);
        for (uint32_t n = 0; n < (1u << 16); n++) {
          const uint32_t t0 = clock();
          while ((uint32_t)clock() - t0 < 300u) {}
          const uint4 v1 = ld_msg<0>(f);
          take(v0);
          if (!todo) break;
          v0 = ld_msg<0>(f);
          take(v1);
          if (!todo) break;
        }
        wait_cnt(&p.cnt[rb * 32 + C_UV + (rk ^ 1) * 4 + cb], epoch);
      }
      __syncwarp();
      bar_sync(1, 288);
      asm volatile("barrier.cluster.wait.aligned;" ::: "memory");
      if (lane == 0) {
        fence_async_smem();
        asm volatile("cp.async.bulk.shared::cluster.shared::cta.mbarrier::complete_tx::bytes [%0], [%1], %2, [%3];"
                     :: "r"(mapa(sm + OFF_STG, rk ^ 1)), "r"(sm + OFF_STG + 16384), "r"(16384), "r"(mapa(bars + BAR_M, rk ^ 1)) : "memory");
      }
    } else {
      const int pc = lane & 15;
      uint4 bq = make_uint4(0, 0, 0, 0), br = bq;
      if (warp == 10) { bq = ldg_nc<0>(p.b1 + colq + pc * 8); br = ldg_nc<0>(p.b1 + (pc < 8 ? colr + pc * 8 : colh + rk * 32 + (pc & 3) * 8)); }
      else {
        const uint32_t b2v = *reinterpret_cast<const uint32_t*>(p.b2 + cb * 128 + rk * 64 + lane * 2);
        *reinterpret_cast<float2*>(smem_raw + OFF_B2 + lane * 8) = make_float2(0.5f * bf_lo(b2v), 0.5f * bf_hi(b2v));
      }
      EPOCH();
      float4* cs = p.cs + ((epoch & 1) * 8 + j) * 96;
      if (rb == 0 && warp == 11) {
#pragma unroll
        for (int i = 0; i < 3; i++) p.cs[(((epoch & 1) ^ 1) * 8 + j) * 96 + i * 32 + lane] = make_float4(0.f, 0.f, 0.f, 0.f);
      }
#pragma unroll 1
      for (int part = 0; part < 2; part++) {
        const int s = rb >> 1, i = s >= NB1 ? s - NB1 : s;
        const uint32_t pp = part && pc >= 8 ? (pc & 3) + rk * 4 : pc & 7;
        const uint32_t a0 = sm + (part ? OFF_STG + (pc >> 3) * 4096 : bslot(i) + (pc >> 3) * 8192 + (rb & 1) * 4096) + ((warp - 10) * 16 + (lane >> 4) * 8) * 128;
        mbar_wait(bars + BAR_HI, part);
        if (!part) mbar_wait(bars + BAR_BF + 8 * i, s >= NB1);
        uint4 v[8];
#pragma unroll
        for (int r = 0; r < 8; r++) v[r] = lds4u(a0 + r * 128 + ((pp ^ r) << 4));
        bar_sync(5, 64);
        if (warp == 10 && lane == 0) mbar_arrive(bars + (part ? BAR_HD : BAR_BE + 8 * i));
        float t[8] = {0.f, 0.f, 0.f, 0.f, 0.f, 0.f, 0.f, 0.f};
#pragma unroll
        for (int r = 0; r < 8; r++) {
          t[0] += bf_lo(v[r].x); t[1] += bf_hi(v[r].x); t[2] += bf_lo(v[r].y); t[3] += bf_hi(v[r].y);
          t[4] += bf_lo(v[r].z); t[5] += bf_hi(v[r].z); t[6] += bf_lo(v[r].w); t[7] += bf_hi(v[r].w);
        }
#pragma unroll
        for (int c = 0; c < 8; c++) t[c] += __shfl_xor_sync(0xffffffffu, t[c], 16);
        float4* d = cs + part * 48 + pc;
        if (lane < 16) {
          asm volatile("red.relaxed.gpu.global.add.v4.f32 [%0], {%1,%2,%3,%4};" :: "l"(d), "f"(t[0]), "f"(t[1]), "f"(t[2]), "f"(1.0f) : "memory");
          asm volatile("red.relaxed.gpu.global.add.v4.f32 [%0], {%1,%2,%3,%4};" :: "l"(d + 16), "f"(t[3]), "f"(t[4]), "f"(t[5]), "f"(1.0f) : "memory");
          asm volatile("red.relaxed.gpu.global.add.v4.f32 [%0], {%1,%2,%3,%4};" :: "l"(d + 32), "f"(t[6]), "f"(t[7]), "f"(0.0f), "f"(1.0f) : "memory");
        }
        mbar_wait(bars + (part ? BAR_FULL + 8 * 3 : BAR_FREE + 8), 0);
        if (!part && warp == 11 && elect_one()) {
          mbar_expect_tx(bars + BAR_HI, 8192);
          tma2d(sm + OFF_STG, &p.mw1s, colr, rb * 32, bars + BAR_HI);
          tma2d(sm + OFF_STG + 4096, &p.mw1s, colh, rb * 32, bars + BAR_HI);
        }
        __syncwarp();
        if (warp == 10) {
          uint4 m0, m1, m2;
          for (uint32_t n = 0; n < (1u << 16); n++) {
            if (lane < 16) { m0 = ld_msg<0>(d); m1 = ld_msg<256>(d); m2 = ld_msg<512>(d); }
            if (__all_sync(0xffffffffu, lane >= 16 || (m0.w == 0x42000000u && m1.w == 0x42000000u && m2.w == 0x42000000u))) break;
            __nanosleep(200);
          }
          const uint4 b = part ? br : bq;
          if (lane < (part ? 12 : 16)) {
            const uint32_t o = sm + OFF_VH + ((part ? 0 : 48) + pc * 4) * 16;
            sts4(o, m0.x, m0.y, __float_as_uint(0.5f * bf_lo(b.x)), __float_as_uint(0.5f * bf_hi(b.x)));
            sts4(o + 16, m0.z, m1.x, __float_as_uint(0.5f * bf_lo(b.y)), __float_as_uint(0.5f * bf_hi(b.y)));
            sts4(o + 32, m1.y, m1.z, __float_as_uint(0.5f * bf_lo(b.z)), __float_as_uint(0.5f * bf_hi(b.z)));
            sts4(o + 48, m2.x, m2.y, __float_as_uint(0.5f * bf_lo(b.w)), __float_as_uint(0.5f * bf_hi(b.w)));
          }
        } else if (!part) {
          const float4* sp = &p.stats[row0 + lane];
          uint2 sv[4];
          for (uint32_t n = 0; n < (1u << 16); n++) {
#pragma unroll
            for (int q = 0; q < 4; q++) sv[q] = ld_msg2(sp + q * 32);
            if (!__any_sync(0xffffffffu, ((sv[0].x ^ tag) | (sv[1].x ^ tag) | (sv[2].x ^ tag) | (sv[3].x ^ tag)) & 3u)) break;
            __nanosleep(200);
          }
#pragma unroll
          for (int q = 0; q < 4; q++) asm volatile("st.shared.v2.u32 [%0], {%1,%2};" :: "r"(sm + OFF_ST + (q * 32 + lane) * 8), "r"(sv[q].x), "r"(sv[q].y) : "memory");
        }
        __syncwarp();
        if (lane == 0 && (!part || warp == 10)) { mbar_arrive(bars + (part ? BAR_V2 : BAR_V)); }
      }
    }
  } else {
    asm volatile("setmaxnreg.inc.sync.aligned.u32 200;");
    Ctx c; c.sm = sm; c.lead = lane == 0; c.lbo96 = (512u + rk * 4u) << 16;
    c.da = (((sm + (warp >> 2) * 8192) & 0x3FFFF) >> 4) | (1u << 16); c.db = (sm & 0x3FFFF) >> 4;
    const int rl = warp * 16 + (lane >> 2);
    float Q[64], R[48], U[64], M[64], Y[64];
    HEpi e;
    e.vec = sm + OFF_VH + (lane & 3) * 16; e.stg = sm + OFF_STG + rl * 64 + (lane & 3) * 16;
    e.never = gridDim.y - 1;
    uint32_t xw[4][4];
    float mu[2] = {0.f, 0.f}, qq[2] = {0.f, 0.f};
    uint32_t pv[2];
    float sa_, sb_, qa_;
    uint32_t xla[4], xsa[2];
#pragma unroll
    for (int t = 0; t < 2; t++) {
      const int kl = t * 4 + (lane >> 3), ks = t * 4 + ((lane & 7) >> 1);
      const int r0 = j * 16 + warp * 2;
      xla[t] = sm + xslot(kl) + r0 * 128 + (((lane & 7) ^ (r0 & 7)) << 4);
      xla[2 + t] = sm + xslot(kl) + (r0 + 1) * 128 + (((lane & 7) ^ ((r0 + 1) & 7)) << 4);
      xsa[t] = sm + OFF_STG + warp * 2048 + ks * 128 + ((((lane & 1) * 4 + (lane >> 3)) ^ ks) << 4);
    }
    const float4* stp = &p.stats[row0 + j * 16 + warp * 2 + (lane >> 1)];
    asm volatile("" : "+r"(xla[0]), "+r"(xla[1]), "+r"(xla[2]), "+r"(xla[3]), "+r"(xsa[0]), "+r"(xsa[1]), "+l"(stp));
    auto xn_piece = [&](auto P_) {
      constexpr int P = decltype(P_)::value;
      if constexpr (P == 0 || P == 4) {
        constexpr int h = P / 4;
#pragma unroll
        for (int k = h ? 4 : 1; k < 4 + 4 * h; k++) mbar_wait(bars + BAR_XF + 8 * k, 0);
#pragma unroll
        for (int r = 0; r < 2; r++) {
          const uint4 v = lds4u(xla[2 * r + h]);
          xw[2 * r + h][0] = v.x; xw[2 * r + h][1] = v.y; xw[2 * r + h][2] = v.z; xw[2 * r + h][3] = v.w;
        }
      }
      if (P == 1) { pv[0] = __byte_perm(__shfl_sync(0xffffffffu, xw[0][0], 0), 0, 0x1010); pv[1] = __byte_perm(__shfl_sync(0xffffffffu, xw[2][0], 0), 0, 0x1010); }
      if constexpr (P == 2 || P == 3 || P == 5 || P == 6) {
        constexpr int h = P > 4, r = h ? P - 5 : P - 2, t = 2 * r + h;
        float a = 0.f, b = 0.f, qa = 0.f, qb = 0.f;
        if constexpr (h) { a = mu[r]; qa = qq[r]; }
#pragma unroll
        for (int i = 0; i < 4; i++) {
          uint32_t d;
          asm volatile("sub.rn.bf16x2 %0, %1, %2;" : "=r"(d) : "r"(xw[t][i]), "r"(pv[r]));
          a += bf_lo(d); b += bf_hi(d); qa = fmaf(bf_lo(d), bf_lo(d), qa); qb = fmaf(bf_hi(d), bf_hi(d), qb);
        }
        mu[r] = a + b; qq[r] = qa + qb;
        if (h) mu[r] = ((lane & 1) ? qq[r] : mu[r]) + __shfl_xor_sync(0xffffffffu, (lane & 1) ? mu[r] : qq[r], 1);
        else asm volatile("{\n.reg .pred p;\nsetp.ne.u32 p, %0, 0;\n@p st.shared.v2.f32 [%1], {%2, %3};\n}" :: "r"(e.never), "r"(e.stg), "f"(mu[r]), "f"(qq[r]) : "memory");
      }
      if (P == 7) {
        sa_ = ((lane & 2) ? mu[1] : mu[0]) + __shfl_xor_sync(0xffffffffu, (lane & 2) ? mu[0] : mu[1], 2);
        sa_ += __shfl_xor_sync(0xffffffffu, sa_, 4);
      }
      if (P == 8) { sa_ += __shfl_xor_sync(0xffffffffu, sa_, 8); sa_ += __shfl_xor_sync(0xffffffffu, sa_, 16); sb_ = __shfl_xor_sync(0xffffffffu, sa_, 1); }
      if (P == 9) {
        const float s1 = ((lane & 1) ? sb_ : sa_) * (1.0f / DM), s2 = (lane & 1) ? sa_ : sb_;
        sa_ = bf_lo((lane & 2) ? pv[1] : pv[0]) + s1;
        sb_ = fmaxf(fmaf(s2, 1.0f / DM, -s1 * s1), 0.f);
        qa_ = rcp_f(bfr(sqrt_f(bfr(bfr(sb_) + 1e-5f))));
        const uint32_t mm = pack2(sa_, sa_);
        pv[0] = __shfl_sync(0xffffffffu, mm, 0); pv[1] = __shfl_sync(0xffffffffu, mm, 2);
      }
      if (P == 8) { wg_wait<0>(); release<3>(c); }
      if (P == 10) {
        const float rh = bfr(qa_);
        const uint32_t hl = pack2(rh, qa_ - rh);
        qq[0] = __uint_as_float(__shfl_sync(0xffffffffu, hl, 0)); qq[1] = __uint_as_float(__shfl_sync(0xffffffffu, hl, 2));
      }
      if constexpr (P >= 11 && P < 15) {
        constexpr int t = P - 11, r = t >> 1;
        const uint32_t hi = __byte_perm(__float_as_uint(qq[r]), 0, 0x1010), lo = __byte_perm(__float_as_uint(qq[r]), 0, 0x3232);
#pragma unroll
        for (int i = 0; i < 4; i++)
          asm("{\n.reg .b32 t;\nsub.rn.bf16x2 %0, %0, %3;\nmul.rn.bf16x2 t, %0, %2;\nfma.rn.bf16x2 %0, %0, %1, t;\n}" : "+r"(xw[t][i]) : "r"(hi), "r"(lo), "r"(pv[r]));
        asm volatile("stmatrix.sync.aligned.m8n8.x4.shared.b16 [%0], {%1,%2,%3,%4};"
                     :: "r"(xsa[t & 1] + r * 1024),
                        "r"(xw[t][0]), "r"(xw[t][1]), "r"(xw[t][2]), "r"(xw[t][3]) : "memory");
        if (t == 3) bar_arrive(1, 288);
      }
      if (P == 15) {
        const float m1 = bfr(sa_), i1 = qa_, i2 = 0.5f * rcp_f(bfr(sqrt_f(bfr(bfr(sb_ * i1 * i1) + 1e-5f))));
        EPOCH();
        if ((lane & ~2) == 0)
          asm volatile("st.relaxed.gpu.global.v4.u32 [%0], {%1,%2,%1,%2};" :: "l"(stp),
                       "r"(tagf(i1 * i2, tag)), "r"(tagf(-(m1 * i1 + bfr((sa_ - m1) * i1)) * i2, tag)) : "memory");
      }
    };
    auto xn_gap_work = [&](auto G_) {
      static_for<0, 16>([&](auto P_) { if constexpr (xn_gap(decltype(P_)::value) == decltype(G_)::value) xn_piece(P_); });
    };
    static_for<0, S_ROLL>([&](auto S_) {
      constexpr int S = decltype(S_)::value;
      constexpr int u = S - HS0;
      float4 hv;
      constexpr int G = u < 0 ? 0 : u < 16 ? u / 4 : (u - 16) / 4, id = 1 + ((1 + u / 4) & 3);
      if constexpr (u >= 0) hv = lds4f(e.vec + hvec(u));
      if constexpr (u >= 0 && u % 4 == 3 && (u >= 16 || G < 2)) mbar_wait(bars + (u == 3 ? BAR_HD : BAR_FREE + 8 * G), u >= 16 && G < 2);
      auto under = [&](auto K_) {
        if constexpr (u >= 0 && decltype(K_)::value == 1) {
          if constexpr (u < 16) h_unit<G, u % 4>(Q, e, hv); else h_unit<G, u % 4>(R, e, hv);
        }
        if constexpr (u >= 0 && u % 4 == 3 && decltype(K_)::value == 2) h_store<G>(e, id);
        if constexpr (decltype(K_)::value == 4 && S > 0) {
          if constexpr (S != 4) release<S - 1>(c);
          if (S == 8) reg_fence(Q);
          if (S == S_S) reg_fence(R);
        }
        if constexpr (decltype(K_)::value != 4) xn_gap_work(IC<S * 4 + decltype(K_)::value>{});
      };
      if constexpr (S < 8) step1<128, S>(Q, c, under);
      else if constexpr (S < S_S) step1<96, S>(R, c, under);
      else step2<1>(U, c, stage_of(S), par_of(S), S > S_S, under);
      if (S == 0 && warp == 0) bar_arrive(6, 64);
      if (S == 7) asm volatile("barrier.cluster.wait.aligned;" ::: "memory");
      xn_gap_work(IC<S * 4 + 3>{});
      if (u == 15) mbar_wait(bars + BAR_V2, 0);
      if (S == HS0 - 1) {
        mbar_wait(bars + BAR_V, 0);
        const float2 t0 = lds2f(sm + OFF_ST + rl * 8), t1 = lds2f(sm + OFF_ST + rl * 8 + 64);
        e.a0 = t0.x; e.b0 = t0.y; e.a1 = t1.x; e.b1 = t1.y;
      }
    });
    int st = stage_of(S_ROLL), pst = stage_of(S_ROLL - 1); uint32_t ph = par_of(S_ROLL);
#pragma unroll 1
    for (int s = S_ROLL; s < S_M; s++) {
      step2<1, 0>(U, c, st, ph, 1, [&](auto K_) { if (decltype(K_)::value == 4) release2(c, pst); });
      pst = st; if (++st == NST) { st = 0; ph ^= 1; }
    }
    const size_t ooff = (size_t)(row0 + rl) * DM + cb * 128 + rk * 64 + (lane & 3) * 8;
    const __nv_bfloat16* xp = p.x + ooff;
    uint4 xr[4];
    static_for<S_M, S_M + 4>([&](auto S_) {
      constexpr int S = decltype(S_)::value;
      step2<1>(M, c, stage_of(S), par_of(S), S > S_M, [&](auto K_) {
        if (decltype(K_)::value == 4) { release<S - 1>(c); if (S == S_M) reg_fence(U); }
      });
      {
        constexpr int G = S - S_M, r = 16 * G;
        mbar_wait(bars + BAR_FREE + 8 * G, G < 2 ? 0 : G == 2 ? 1 : 0);
        sts4(e.stg + G * 8192, pack2(U[r], U[r + 1]), pack2(U[r + 4], U[r + 5]), pack2(U[r + 8], U[r + 9]), pack2(U[r + 12], U[r + 13]));
        sts4(e.stg + G * 8192 + 512, pack2(U[r + 2], U[r + 3]), pack2(U[r + 6], U[r + 7]), pack2(U[r + 10], U[r + 11]), pack2(U[r + 14], U[r + 15]));
        bar_arrive(1 + G, 288);
        xr[G] = ldg_nc<(G & 1) * 16 * DM + (G >> 1) * 64>(xp);
      }
    });
    st = stage_of(S_M + 4); pst = stage_of(S_M + 4 - 1); ph = par_of(S_M + 4);
#pragma unroll 1
    for (int s = S_M + 4; s < S_Y; s++) {
      step2<1, 0>(M, c, st, ph, 1, [&](auto K_) { if (decltype(K_)::value == 4) release2(c, pst); });
      pst = st; if (++st == NST) { st = 0; ph ^= 1; }
    }
    const uint32_t mine = warp * 2048 + lane * 16, peer = rk ^ 1, sgn = rk ? 0x80008000u : 0u;
    uint4 g[4], mr[4];
    auto gate = [&](auto U_) {
      constexpr int u = decltype(U_)::value, G = u >> 1, H = u & 1;
      uint32_t w[4];
#pragma unroll
      for (int i = 0; i < 4; i++) {
        const int r = 4 * (4 * G + i) + 2 * H;
        const uint4 t4 = mr[2 * G + (i >> 1)];
        const uint32_t t = (i & 1) ? (H ? t4.w : t4.z) : (H ? t4.y : t4.x);
        const float z0 = fmaf(bf_lo(t), 0.5f, M[r]), z1 = fmaf(bf_hi(t), 0.5f, M[r + 1]);
        w[i] = pack2(fmaf(z0, tanh_f(z0), z0), fmaf(z1, tanh_f(z1), z1)) ^ sgn;
      }
      asm volatile("stmatrix.sync.aligned.m8n8.x4.shared.b16 [%0], {%1,%2,%3,%4};"
                   :: "r"(sm + OFF_STG + warp * 2048 + u * 512 + (lane & 7) * 64 + (((lane >> 3) ^ ((lane >> 1) & 3)) << 4)),
                      "r"(w[0]), "r"(w[1]), "r"(w[2]), "r"(w[3]) : "memory");
    };
    static_for<S_Y, S_END>([&](auto S_) {
      constexpr int S = decltype(S_)::value;
      float2 bv[4];
      if constexpr (S == S_Y + 2 || S == S_Y + 3) {
#pragma unroll
        for (int i = 0; i < 4; i++) bv[i] = lds2f(sm + OFF_B2 + (S == S_Y + 3 ? 128 : 0) + 32 * i + (lane & 3) * 8);
      }
      step2<0>(Y, c, stage_of(S), par_of(S), S > S_Y, [&](auto K_) {
        constexpr int K = decltype(K_)::value;
        if (K == 4) { release<S - 1>(c); if (S == S_Y) reg_fence(M); }
        if constexpr (K == 1 && (S == S_Y + 2 || S == S_Y + 3)) {
          constexpr int G = S - S_Y - 2;
#pragma unroll
          for (int i = 0; i < 4; i++) {
            const int r = 4 * (4 * G + i);
            M[r] = fmaf(M[r], 0.5f, bv[i].x); M[r + 1] = fmaf(M[r + 1], 0.5f, bv[i].y); M[r + 2] = fmaf(M[r + 2], 0.5f, bv[i].x); M[r + 3] = fmaf(M[r + 3], 0.5f, bv[i].y);
          }
          asm volatile("{\n.reg .pred p;\nsetp.ne.u32 p, %0, 0;\n@p st.shared.v4.f32 [%1], {%2, %3, %4, %5};\n}"
                       :: "r"(e.never), "r"(e.stg), "f"(M[16 * G] + M[16 * G + 4]), "f"(M[16 * G + 9]), "f"(M[16 * G + 14]), "f"(M[16 * G + 15]) : "memory");
        }
        if constexpr (K == 1 && S > S_Y + GW) gate(IC<(S > S_Y + GW ? S - S_Y - GW - 1 : 0)>{});
      });
      if (S == S_Y) {
#pragma unroll
        for (int v = 0; v < 4; v++)
          sts4(sm + OFF_STG + 16384 + mine + v * 512, pack2(M[32 + 8 * v], M[33 + 8 * v]), pack2(M[34 + 8 * v], M[35 + 8 * v]), pack2(M[36 + 8 * v], M[37 + 8 * v]), pack2(M[38 + 8 * v], M[39 + 8 * v]));
        bar_arrive(1, 288);
      }
      if (S == S_END - NST + 1 && c.lead) mbar_arrive_cluster(mapa(bars + BAR_OK, peer));
      if (S == S_Y + GW) {
        mbar_wait(bars + BAR_M, 0);
#pragma unroll
        for (int v = 0; v < 4; v++) mr[v] = lds4u(sm + OFF_STG + mine + v * 512);
        __syncwarp();
      }
    });
    static_for<S_END - 1 - S_Y - GW, 4>(gate);
    __syncwarp();
#pragma unroll
    for (int v = 0; v < 4; v++) g[v] = lds4u(sm + OFF_STG + warp * 2048 + v * 512 + (lane >> 2) * 64 + (((lane & 3) ^ ((lane >> 3) & 3)) << 4));
    mbar_wait(bars + BAR_OK, 0);
    const uint32_t rl_ = mapa(sm + LAND_STAGE * STB + mine, peer), ybar = bars + (warp < 4 ? BAR_Y : BAR_Y1), rlb = mapa(ybar, peer);
    wg_wait<0>();
    reg_fence(Y);
#pragma unroll
    for (int v = 0; v < 4; v++)
      st_async4(rl_ + v * 512, pack2(Y[32 + 8 * v], Y[33 + 8 * v]), pack2(Y[34 + 8 * v], Y[35 + 8 * v]), pack2(Y[36 + 8 * v], Y[37 + 8 * v]), pack2(Y[38 + 8 * v], Y[39 + 8 * v]), rlb);
    float gf[32];
#pragma unroll
    for (int G = 0; G < 2; G++) {
#pragma unroll
      for (int H = 0; H < 2; H++) {
        const uint32_t gw[4] = {g[2 * G + H].x, g[2 * G + H].y, g[2 * G + H].z, g[2 * G + H].w};
        const uint32_t xq[4] = {xr[2 * G + H].x, xr[2 * G + H].y, xr[2 * G + H].z, xr[2 * G + H].w};
#pragma unroll
        for (int i = 0; i < 4; i++) {
          const int a = 4 * (4 * G + i) + 2 * H;
          gf[a] = -bf_lo(gw[i]); gf[a + 1] = -bf_hi(gw[i]);
          Y[a] = fmaf(Y[a], -gf[a], bf_lo(xq[i])); Y[a + 1] = fmaf(Y[a + 1], -gf[a + 1], bf_hi(xq[i]));
        }
      }
    }
#pragma unroll
    for (int i = 0; i < 32; i += 4) asm volatile("" : "+f"(Y[i]), "+f"(Y[i + 1]), "+f"(Y[i + 2]), "+f"(Y[i + 3]), "+f"(gf[i]), "+f"(gf[i + 1]), "+f"(gf[i + 2]), "+f"(gf[i + 3]) :: "memory");
    asm volatile("{\n.reg .pred p;\nsetp.ne.u32 p, %0, 0;\n@p st.shared.v4.f32 [%1], {%2, %3, %4, %5};\n}"
                 :: "r"(e.never), "r"(e.stg), "f"(Y[0] + Y[5] + Y[10] + Y[15]), "f"(Y[16] + Y[21] + Y[26] + Y[31]), "f"(Y[3] + Y[6] + Y[9] + Y[12]), "f"(Y[19] + Y[22] + Y[25] + Y[28]) : "memory");
    mbar_wait(ybar, 0);
#pragma unroll
    for (int G = 0; G < 2; G++) {
      uint32_t o0[4], o1[4];
      const uint4 tv[2] = {lds4u(sm + LAND_STAGE * STB + mine + 2 * G * 512), lds4u(sm + LAND_STAGE * STB + mine + (2 * G + 1) * 512)};
#pragma unroll
      for (int i = 0; i < 4; i++) {
        const int a = 4 * (4 * G + i);
        const uint32_t t0 = (i & 1) ? tv[i >> 1].z : tv[i >> 1].x, t1 = (i & 1) ? tv[i >> 1].w : tv[i >> 1].y;
        o0[i] = pack2(fmaf(bf_lo(t0), gf[a], Y[a]), fmaf(bf_hi(t0), gf[a + 1], Y[a + 1]));
        o1[i] = pack2(fmaf(bf_lo(t1), gf[a + 2], Y[a + 2]), fmaf(bf_hi(t1), gf[a + 3], Y[a + 3]));
      }
      stg4(p.out + ooff + 32 * G, o0[0], o0[1], o0[2], o0[3]);
      stg4(p.out + ooff + 32 * G + 8 * DM, o1[0], o1[1], o1[2], o1[3]);
    }
  }
  } else {
      mbar_wait(bars + BAR_XF, 0); bar_sync(6, 64);
      if (elect_one()) {
        const CUtensorMap* mc = rk ? &p.mci : &p.mcr;
        const CUtensorMap* md = rk ? &p.mdim : &p.mdre;
        asm volatile("prefetch.tensormap [%0];" :: "l"(&p.mw1h) : "memory");
        asm volatile("prefetch.tensormap [%0];" :: "l"(mc) : "memory");
        asm volatile("prefetch.tensormap [%0];" :: "l"(&p.mxn) : "memory");
        asm volatile("prefetch.tensormap [%0];" :: "l"(&p.mh) : "memory");
        asm volatile("prefetch.tensormap [%0];" :: "l"(&p.mw2) : "memory");
        asm volatile("prefetch.tensormap [%0];" :: "l"(&p.muv) : "memory");
        asm volatile("prefetch.tensormap [%0];" :: "l"(md) : "memory");
        for (int k = NB1, i = 0, par = 0; k < S_S; k++) {
          const uint32_t fb = bars + BAR_BF + 8 * i;
          mbar_block(bars + BAR_BE + 8 * i, par);
          mbar_expect_tx(fb, 16384);
          if (k < 8) tma3d(sm + bslot(i), &p.mw1, colq, k * 64, 0, fb);
          else { tma2d(sm + bslot(i), &p.mw1h, colr, (k & 7) * 64, fb); tma2d(sm + bslot(i) + 8192, &p.mw1h, colh, (k & 7) * 64, fb); }
          mbar_arrive(bars + (k == (rb >> 1) ? BAR_HI : BAR_BE + 8 * i));
          if (++i == NB1) { i = 0; par ^= 1; }
        }
        const int n0 = cb * 128 + rk * 64, n1 = cb * 128 + (rk ^ 1) * 64;
        auto acquire = [&](int st, uint32_t ph) { mbar_block(bars + BAR_EMPTY + 8 * st, ph); mbar_expect_tx(bars + BAR_FULL + 8 * st, STB); };
        mbar_wait(bars + BAR_DEP, 0);
        asm volatile("fence.proxy.async.global;" ::: "memory");
#pragma unroll 1
        for (int k0 = 0, ph = 0; k0 < 32 * 64; k0 += NST * 64, ph ^= 1) {
          static_for<0, NST>([&](auto I_) {
            constexpr int st = decltype(I_)::value;
            if (st < 2 || k0 < 30 * 64) {
              acquire(st, ph);
              tma2d(sm + st * STB, mc, k0 + st * 64, row0, bars + BAR_FULL + 8 * st);
              tma3d(sm + st * STB + 16384, &p.mxn, 0, k0 + st * 64, cb * 2, bars + BAR_FULL + 8 * st);
            }
          });
        }
        mbar_wait(bars + BAR_DEP, 1);
        asm volatile("fence.proxy.async.global;" ::: "memory");
        static_for<S_M, S_Y>([&](auto S_) {
          constexpr int S = decltype(S_)::value, st = stage_of(S);
          const int k = rk * 14 + (S - S_M);
          acquire(st, par_of(S));
          tma2d(sm + st * STB, &p.mh, k * 64, row0, bars + BAR_FULL + 8 * st);
          tma5d(sm + st * STB + 16384, &p.mw2, n0, 2 * k, bars + BAR_FULL + 8 * st);
          tma5d(sm + st * STB + 24576, &p.mw2, n1, 2 * k, bars + BAR_FULL + 8 * st);
        });
        red_add(&p.cnt[rb * 32 + C_DONE]);
        static_for<S_Y, S_END>([&](auto S_) {
          constexpr int S = decltype(S_)::value, st = stage_of(S), k = S - S_Y;
          acquire(st, par_of(S));
          tma5d(sm + st * STB + 16384, md, k * 64, n0 >> 5, bars + BAR_FULL + 8 * st);
          tma5d(sm + st * STB + 24576, md, k * 64, n1 >> 5, bars + BAR_FULL + 8 * st);
          if (!(k & 1)) { mbar_wait(bars + BAR_DU + 4 * k, 0); asm volatile("fence.proxy.async.global;" ::: "memory"); }
          tma2d(sm + st * STB, &p.muv, k * 64, rk * SEQ + row0, bars + BAR_FULL + 8 * st);
        });
      }
  }
}

typedef CUresult (*EncFn)(CUtensorMap*, CUtensorMapDataType, cuuint32_t, void*, const cuuint64_t*, const cuuint64_t*, const cuuint32_t*,
                          const cuuint32_t*, CUtensorMapInterleave, CUtensorMapSwizzle, CUtensorMapL2promotion, CUtensorMapFloatOOBfill);

void make_map(EncFn enc, CUtensorMap* m, const void* ptr, int nd, const uint64_t* dims, const uint64_t* strides, const uint32_t* box,
              CUtensorMapSwizzle sw = CU_TENSOR_MAP_SWIZZLE_128B) {
  const cuuint32_t es[5] = {1, 1, 1, 1, 1};
  cuuint64_t d[5], s[5]; cuuint32_t b[5];
  for (int i = 0; i < nd; i++) { d[i] = dims[i]; b[i] = box[i]; if (i + 1 < nd) s[i] = strides[i]; }
  enc(m, CU_TENSOR_MAP_DATA_TYPE_BFLOAT16, nd, const_cast<void*>(ptr), d, s, b, es, CU_TENSOR_MAP_INTERLEAVE_NONE,
      sw, CU_TENSOR_MAP_L2_PROMOTION_L2_128B, CU_TENSOR_MAP_FLOAT_OOB_FILL_NONE);
}

}

extern "C" void kernel_launch(void* const* d_in, const int* in_sizes, int n_in, void* d_out, int out_size) {
  static Params prm;
  static const void* key[11];
  static EncFn enc = nullptr;
  bool same = enc != nullptr && key[10] == d_out;
  for (int i = 0; i < 10 && same; i++) same = key[i] == d_in[i];
  if (!same) {
    if (!enc) {
      cudaDriverEntryPointQueryResult q;
      cudaGetDriverEntryPoint("cuTensorMapEncodeTiled", reinterpret_cast<void**>(&enc), cudaEnableDefault, &q);
      cudaFuncSetAttribute(fused_kernel, cudaFuncAttributeMaxDynamicSharedMemorySize, SMEM_BYTES);
    }
    void *xn, *uv, *h;
    cudaGetSymbolAddress(&xn, g_xn);
    cudaGetSymbolAddress(&uv, g_uv);
    cudaGetSymbolAddress(&h, g_h);
    const uint64_t R = DM * 2;
    const uint32_t box2[2] = {64, 128}, box3[3] = {64, 64, 2}, box5[5] = {64, 2, 4, 4, 2}, boxs[2] = {32, 128};
    { const uint64_t d[2] = {DM, SEQ}, s[1] = {R}; make_map(enc, &prm.mx, d_in[0], 2, d, s, box2); }
    { const uint64_t d[2] = {64, SEQ * 8}, s[1] = {128}; make_map(enc, &prm.sxn, xn, 2, d, s, box2); }
    { const uint64_t d[3] = {64, SEQ, 8}, s[2] = {R, 128}; make_map(enc, &prm.mxn, xn, 3, d, s, box3); }
    { const uint64_t d[2] = {SEQ, SEQ}, s[1] = {SEQ * 2}; make_map(enc, &prm.mcr, d_in[1], 2, d, s, box2); make_map(enc, &prm.mci, d_in[2], 2, d, s, box2); }
    { const uint64_t d[5] = {DM, 2, 4, 4, DM / 32}, s[4] = {R, 8 * R, 2 * R, 32 * R};
      make_map(enc, &prm.mdre, d_in[3], 5, d, s, box5); make_map(enc, &prm.mdim, d_in[4], 5, d, s, box5); }
    { const uint64_t d[3] = {FF, DM, 2}, s[2] = {FF * 2, 128}; make_map(enc, &prm.mw1, d_in[6], 3, d, s, box3);
      const uint32_t b[2] = {64, 64}, bs[2] = {64, 32}; make_map(enc, &prm.mw1h, d_in[6], 2, d, s, b); make_map(enc, &prm.mw1s, d_in[6], 2, d, s, bs); }
    { const uint64_t d[2] = {FF, SEQ}, s[1] = {FF * 2}; make_map(enc, &prm.mh, h, 2, d, s, box2); make_map(enc, &prm.sh, h, 2, d, s, boxs, CU_TENSOR_MAP_SWIZZLE_NONE); }
    { const uint64_t d[5] = {DM, 2, 4, 4, FF / 32}, s[4] = {R, 8 * R, 2 * R, 32 * R}; make_map(enc, &prm.mw2, d_in[8], 5, d, s, box5); }
    { const uint64_t d[2] = {DM, 2 * SEQ}, s[1] = {R}; make_map(enc, &prm.muv, uv, 2, d, s, box2); make_map(enc, &prm.suv, uv, 2, d, s, boxs, CU_TENSOR_MAP_SWIZZLE_NONE); }
    cudaGetSymbolAddress((void**)&prm.stats, g_stats); cudaGetSymbolAddress((void**)&prm.cs, g_cs); cudaGetSymbolAddress((void**)&prm.cnt, g_cnt);
    prm.x = (const __nv_bfloat16*)d_in[0]; prm.b1 = (const __nv_bfloat16*)d_in[7]; prm.b2 = (const __nv_bfloat16*)d_in[9];
    prm.out = (__nv_bfloat16*)d_out;
    for (int i = 0; i < 10; i++) key[i] = d_in[i];
    key[10] = d_out;
  }
  fused_kernel<<<128, 384, SMEM_BYTES>>>(prm);
}
```
